```python
import torch

def _softmax(x, axis=-1):
    return torch.softmax(x, dim=axis)

def _gelu(x):
    return torch.nn.functional.gelu(x, approximate='tanh')

def _silu(x):
    return torch.nn.functional.silu(x)

def _sigmoid(x):
    return torch.sigmoid(x)

def _layernorm(x, axis=-1, eps=1e-05):
    m = x.mean(dim=axis, keepdim=True)
    v = x.var(dim=axis, keepdim=True, unbiased=False)
    return (x - m) / torch.sqrt(v + eps)

def _scatter_add(tgt, idx, src, axis=0):
    return tgt.clone().index_add_(axis, idx, src)

def _segment_sum(src, seg, n):
    out = torch.zeros((n,) + src.shape[1:], dtype=src.dtype)
    return out.index_add_(0, seg, src)

def _pad(x, pw):
    flat = tuple((v for pair in reversed(pw) for v in pair))
    return torch.nn.functional.pad(x, flat)
kernel_name = 'adaLN_cond__sliding_block_cached__glu_gated_reglu__decode'

def setup_inputs():

    _w = lambda a: (lambda t: t.to(torch.bfloat16) if t.is_floating_point() else t)(torch.as_tensor(a))

    def _A_setup():
        B, Sq, D = (2, 1, 576)
        Hq, Hkv, Sk, Dh = (32, 16, 32768, 128)
        assert Hq % Hkv == 0, (Hq, Hkv)
        return {'x': _w((lambda *s: torch.randn(*s, dtype=torch.bfloat16) * 0.1)(B, Sq, D)), 'k_cache': _w((lambda *s: torch.randn(*s, dtype=torch.bfloat16) * 0.8)(B, Hkv, Sk, Dh)), 'v_cache': _w((lambda *s: torch.randn(*s, dtype=torch.bfloat16) * 3.2)(B, Hkv, Sk, Dh)), 'wq': _w((lambda *s: torch.randn(*s, dtype=torch.bfloat16) * 0.8)(D, Hq * Dh) * D ** (-0.5)), 'wo': _w((lambda *s: torch.randn(*s, dtype=torch.bfloat16) * 3.2)(Hq * Dh, D) * (Hq * Dh) ** (-0.5))}
    _A_in = _A_setup()

    def _B_setup():
        B, S, D, F = (2, 1, 576, 4608)
        return {'x': _w((lambda *s: torch.randn(*s, dtype=torch.bfloat16) * 0.1)(B, S, D)), 'W_gate': _w((lambda *s: torch.randn(*s, dtype=torch.bfloat16) * 3.2)(D, F) * (2.0 / D) ** 0.5), 'W_up': _w((lambda *s: torch.randn(*s, dtype=torch.bfloat16) * 3.2)(D, F) * (2.0 / D) ** 0.5), 'W_down': _w((lambda *s: torch.randn(*s, dtype=torch.bfloat16) * 3.2)(F, D) * (1.0 / F) ** 0.5)}
    _B_in = _B_setup()
    return {'A_x': _A_in['x'], 'A_k_cache': _A_in['k_cache'], 'A_v_cache': _A_in['v_cache'], 'A_wq': _A_in['wq'], 'A_wo': _A_in['wo'], 'B_x': _B_in['x'], 'B_W_gate': _B_in['W_gate'], 'B_W_up': _B_in['W_up'], 'B_W_down': _B_in['W_down'], 'c': _w((lambda *s: torch.randn(*s, dtype=torch.bfloat16) * 0.8)(2, 576) * 8.0), 'w_mod': _w((lambda *s: torch.randn(*s, dtype=torch.bfloat16) * 0.8)(576, 6 * 576) * 576 ** (-0.5) * 8.0)}

def reference(A_x, A_k_cache, A_v_cache, A_wq, A_wo, B_x, B_W_gate, B_W_up, B_W_down, c, w_mod):

    def _A_ref(x, k_cache, v_cache, wq, wo):
        B, Sq, D = x.shape
        Hq, Dh = (32, 128)
        Hkv, Sk = (k_cache.shape[1], k_cache.shape[2])
        W = min(4096, max(256, Sk // 4))
        rep = Hq // Hkv
        q = (lambda x, *d: x.permute(*d))((x @ wq).reshape(B, Sq, Hq, Dh), 0, 2, 1, 3)
        k = (lambda x, n, axis: torch.repeat_interleave(x, n, dim=axis))(k_cache[:, :, Sk - W:, :], rep, axis=1)
        v = (lambda x, n, axis: torch.repeat_interleave(x, n, dim=axis))(v_cache[:, :, Sk - W:, :], rep, axis=1)
        scores = torch.einsum('bhqd,bhkd->bhqk', q, k) * Dh ** (-0.5)
        p = _softmax(scores, axis=-1)
        o = torch.einsum('bhqk,bhkd->bhqd', p, v)
        return (lambda x, *d: x.permute(*d))(o, 0, 2, 1, 3).reshape(B, Sq, Hq * Dh) @ wo

    def _B_ref(x, W_gate, W_up, W_down):
        gate = torch.einsum('bsd,df->bsf', x, W_gate)
        up = torch.einsum('bsd,df->bsf', x, W_up)
        gate = gate * (lambda x, dt: x.to(dt))(gate > 0, gate.dtype)
        h = gate * up
        return torch.einsum('bsf,fd->bsd', h, W_down)
    x = A_x
    mod = (_silu(c) @ w_mod).reshape(c.shape[0], 6, 1, -1)
    sa, ca, ga, sb, cb, gb = (mod[:, 0].clone(), mod[:, 1].clone(), mod[:, 2].clone(), mod[:, 3].clone(), mod[:, 4].clone(), mod[:, 5].clone())
    h = _layernorm(x, axis=-1) * (1 + ca) + sa
    x = x + ga * _A_ref(h, A_k_cache, A_v_cache, A_wq, A_wo)
    h = _layernorm(x, axis=-1) * (1 + cb) + sb
    x = x + gb * _B_ref(h, B_W_gate, B_W_up, B_W_down)
    return x
```

```cpp
#include <cuda_runtime.h>
#include <cuda.h>
#include <cuda_bf16.h>
#include <stdint.h>

namespace {

constexpr int DM = 576;
constexpr int FF = 4608;
constexpr int SK = 32768;
constexpr int WIN = 4096;
constexpr int NCTA = 128;
constexpr int NHELP = 4;
constexpr int NTHR = 384;
constexpr int NRED = 36;
constexpr int RED_WARP = 8;

constexpr int WIN_MID = 40, WIN_END = 48, WIN_TAIL = 32, WIN_LAST = 36;
constexpr int WIN_HEAVY_EXTRA = 12, END_CHUNKS = 8;
constexpr int PACE_T0 = -400, PACE_TV = 23200, PACE_TV_HEAVY = 23000, PACE_TE = 29700;
constexpr int PACE_MID = 3, PACE_STEP = 8, PACE_SHIFT = 8;
constexpr int PACE_WMIN = 18, PACE_WMAX = 64, TAIL_UP = 8;
constexpr int ANCHOR_BACK = 4, ANCHOR_BIAS = 650;
constexpr int K_AT_START = 2;
constexpr int REP1 = 4;
constexpr int RCNT = 8, RCNT0 = 4;
constexpr unsigned HINT_MOD = 36, HINT_AO = 112, HINT_X1 = 28;
constexpr int PREWRITE_AT = 54;
constexpr int SLEEP_NS = 100;
constexpr unsigned SPIN_LIMIT = 1u << 22;

constexpr int CH = 8192;
constexpr int NS = 26;
constexpr int S0 = 14;
constexpr int OFF_WMOD = 40960;
constexpr int OFF_WQ = 77824;
constexpr int OFF_WO = 0;
constexpr int OFF_GU = 36864;
constexpr int OFF_GX = 110592;
constexpr int OFF_DN = 147456;
constexpr int OFF_SC = NS * CH;
constexpr int OFF_P = OFF_SC + 8192;
constexpr int OFF_Q = OFF_P + 4096;
constexpr int OFF_ST = OFF_Q + 512;
constexpr int OFF_HH = OFF_ST + 256;
constexpr int OFF_R2 = OFF_HH + 256;
constexpr int OFF_OB = OFF_R2 + 1024;
constexpr int OFF_BAR = OFF_OB + 128;
constexpr int SMEM_BYTES = OFF_BAR + 192 * 8 + 1024;
static_assert(SMEM_BYTES <= 232448, "smem");

constexpr int U_KV = 3;
constexpr int U_WO = 67;
constexpr int U_GU = 71;
constexpr int U_WQ = 80;
constexpr int U_GX = 83;
constexpr int U_DN = 89;
constexpr int B_DONE = 95;
constexpr int B_MODFREE = 96, B_WQFREE = 97;
constexpr int B_GATE_AO = 98, B_GATE_X1 = 99, B_GATE_MOD = 100;
constexpr int B_USED = 128;

enum { M_WMOD, M_WQ, M_K, M_V, M_WO, M_DN, M_GATE, M_UP, M_GATEX, M_UPX, M_COUNT };
constexpr int NOPS_LIGHT = 84, NOPS_HEAVY = 89, NOPS_HELP = 9;
struct Params { CUtensorMap m[M_COUNT]; uint4 op[NOPS_LIGHT + NOPS_HEAVY + NOPS_HELP]; };

enum { C_AO, C_X1, C_SPARE, C_MOD, C_COUNT };
struct __align__(128) Scratch {
    unsigned int epoch;
    unsigned int pad[31];
    unsigned int cnt[3][C_COUNT][RCNT][32];
    unsigned long long ex_mod[REP1 * 6 * DM];
    unsigned long long ex_q[2 * 2048];
    unsigned long long ex_x1[DM];
    unsigned long long ex_ml[NCTA * 4];
    uint32_t ex_o[NCTA * 256];
    uint32_t ex_part[NCTA * DM * 2];
};
__device__ Scratch g_scratch;

__device__ __forceinline__ uint32_t fu(float x) { return __float_as_uint(x); }
__device__ __forceinline__ float uf(uint32_t x) { return __uint_as_float(x); }
__device__ __forceinline__ uint32_t now_ns() { uint32_t t; asm volatile("mov.u32 %0, %globaltimer_lo;" : "=r"(t)); return t; }
__device__ __forceinline__ void mbar_init(uint32_t b, int c) {
    asm volatile("mbarrier.init.shared::cta.b64 [%0], %1;" ::"r"(b), "r"(c) : "memory");
}
__device__ __forceinline__ void mbar_init_fence() { asm volatile("fence.mbarrier_init.release.cluster;" ::: "memory"); }
__device__ __forceinline__ void mbar_expect(uint32_t b, uint32_t bytes) {
    asm volatile("mbarrier.arrive.expect_tx.shared::cta.b64 _, [%0], %1;" ::"r"(b), "r"(bytes) : "memory");
}
__device__ __forceinline__ void mbar_arrive_if(uint32_t b, uint32_t cnt, bool p) {
    asm volatile("{\n.reg .pred p;\nsetp.ne.u32 p, %2, 0;\n@p mbarrier.arrive.shared::cta.b64 _, [%0], %1;\n}"
                 ::"r"(b), "r"(cnt), "r"((uint32_t)p) : "memory");
}
__device__ __forceinline__ bool mbar_try(uint32_t b) {
    uint32_t ok;
    asm volatile("{\n.reg .pred p;\nmbarrier.try_wait.parity.shared::cta.b64 p, [%1], 0;\nselp.u32 %0, 1, 0, p;\n}"
                 : "=r"(ok) : "r"(b) : "memory");
    return ok;
}
__device__ __forceinline__ bool mbar_test(uint32_t b) {
    uint32_t ok;
    asm volatile("{\n.reg .pred p;\nmbarrier.test_wait.parity.shared::cta.b64 p, [%1], 0;\nselp.u32 %0, 1, 0, p;\n}"
                 : "=r"(ok) : "r"(b) : "memory");
    return ok;
}
__device__ __forceinline__ void mbar_wait(uint32_t b) {
    unsigned n = 0;
    while (!mbar_try(b))
        if (++n > SPIN_LIMIT) __trap();
}
__device__ __forceinline__ void tma3d(uint32_t dst, const CUtensorMap* m, int c0, int c1, uint32_t bar) {
    asm volatile("cp.async.bulk.tensor.3d.shared::cluster.global.mbarrier::complete_tx::bytes [%0], [%1, {%3, %4, %5}], [%2];"
                 ::"r"(dst), "l"(m), "r"(bar), "r"(c0), "r"(c1), "r"(0) : "memory");
}
__device__ __forceinline__ void tma3d_hint(uint32_t dst, const CUtensorMap* m, int c0, int c1, uint32_t bar, uint64_t pol) {
    asm volatile("cp.async.bulk.tensor.3d.shared::cluster.global.mbarrier::complete_tx::bytes.L2::cache_hint [%0], [%1, {%3, %4, %5}], [%2], %6;"
                 ::"r"(dst), "l"(m), "r"(bar), "r"(c0), "r"(c1), "r"(0), "l"(pol) : "memory");
}
__device__ __forceinline__ bool elect_one() {
    uint32_t p;
    asm volatile("{\n.reg .pred p;\nelect.sync _|p, 0xffffffff;\nselp.u32 %0, 1, 0, p;\n}" : "=r"(p));
    return p;
}
__device__ __forceinline__ uint32_t ldg32(const void* p) {
    uint32_t v;
    asm volatile("ld.global.nc.u32 %0, [%1];" : "=r"(v) : "l"(p));
    return v;
}
__device__ __forceinline__ void bar_comp() { asm volatile("bar.sync 1, 288;" ::: "memory"); }
__device__ __forceinline__ void bar_256() { asm volatile("bar.sync 2, 256;" ::: "memory"); }
__device__ __forceinline__ void sts16(uint32_t a, uint32_t v) { asm volatile("st.shared.b16 [%0], %1;" ::"r"(a), "h"((unsigned short)v) : "memory"); }
__device__ __forceinline__ void sts32_if(uint32_t a, uint32_t v, bool p) {
    asm volatile("{\n.reg .pred p;\nsetp.ne.u32 p, %2, 0;\n@p st.shared.b32 [%0], %1;\n}" ::"r"(a), "r"(v), "r"((uint32_t)p) : "memory");
}
__device__ __forceinline__ void sts64_if(uint32_t a, uint32_t v0, uint32_t v1, bool p) {
    asm volatile("{\n.reg .pred p;\nsetp.ne.u32 p, %3, 0;\n@p st.shared.v2.b32 [%0], {%1, %2};\n}" ::"r"(a), "r"(v0), "r"(v1), "r"((uint32_t)p) : "memory");
}
__device__ __forceinline__ void sts128_if(uint32_t a, uint32_t v0, uint32_t v1, uint32_t v2, uint32_t v3, bool p) {
    asm volatile("{\n.reg .pred p;\nsetp.ne.u32 p, %5, 0;\n@p st.shared.v4.b32 [%0], {%1, %2, %3, %4};\n}"
                 ::"r"(a), "r"(v0), "r"(v1), "r"(v2), "r"(v3), "r"((uint32_t)p) : "memory");
}
__device__ __forceinline__ float lds_f(uint32_t a) { float v; asm volatile("ld.shared.f32 %0, [%1];" : "=f"(v) : "r"(a) : "memory"); return v; }
__device__ __forceinline__ float2 lds_f2(uint32_t a) {
    float2 v; asm volatile("ld.shared.v2.f32 {%0,%1}, [%2];" : "=f"(v.x), "=f"(v.y) : "r"(a) : "memory"); return v;
}
__device__ __forceinline__ float4 lds_f4(uint32_t a) {
    float4 v; asm volatile("ld.shared.v4.f32 {%0,%1,%2,%3}, [%4];" : "=f"(v.x), "=f"(v.y), "=f"(v.z), "=f"(v.w) : "r"(a) : "memory"); return v;
}
__device__ __forceinline__ uint4 lds128(uint32_t addr) {
    uint4 v;
    asm volatile("ld.shared.v4.u32 {%0,%1,%2,%3}, [%4];" : "=r"(v.x), "=r"(v.y), "=r"(v.z), "=r"(v.w) : "r"(addr) : "memory");
    return v;
}
__device__ __forceinline__ void ldsm4t(uint32_t (&a)[4], uint32_t addr) {
    asm volatile("ldmatrix.sync.aligned.m8n8.x4.trans.shared.b16 {%0,%1,%2,%3}, [%4];"
                 : "=r"(a[0]), "=r"(a[1]), "=r"(a[2]), "=r"(a[3]) : "r"(addr) : "memory");
}
__device__ __forceinline__ void mma(float (&c)[4], uint32_t a0, uint32_t a1, uint32_t a2, uint32_t a3, uint32_t b0, uint32_t b1) {
    asm volatile("mma.sync.aligned.m16n8k16.row.col.f32.bf16.bf16.f32 {%0,%1,%2,%3}, {%4,%5,%6,%7}, {%8,%9}, {%0,%1,%2,%3};"
                 : "+f"(c[0]), "+f"(c[1]), "+f"(c[2]), "+f"(c[3])
                 : "r"(a0), "r"(a1), "r"(a2), "r"(a3), "r"(b0), "r"(b1));
}
__device__ __forceinline__ void mma(float (&c)[4], const uint32_t (&a)[4], uint32_t b0, uint32_t b1) {
    mma(c, a[0], a[1], a[2], a[3], b0, b1);
}

template <bool ATOM>
__device__ __forceinline__ void rd16(unsigned long long& a, unsigned long long& b, const void* p, uint32_t on) {
    if (ATOM)
        asm volatile("{\n.reg .pred p;\n.reg .b128 z, d;\nsetp.ne.u32 p, %3, 0;\nmov.b128 z, {0, 0};\nmov.b128 d, {%0, %1};\n"
                     "@p atom.relaxed.gpu.global.cas.b128 d, [%2], z, z;\nmov.b128 {%0, %1}, d;\n}"
                     : "+l"(a), "+l"(b) : "l"(p), "r"(on) : "memory");
    else
        asm volatile("{\n.reg .pred p;\nsetp.ne.u32 p, %3, 0;\n@p ld.relaxed.gpu.global.v2.b64 {%0, %1}, [%2];\n}"
                     : "+l"(a), "+l"(b) : "l"(p), "r"(on) : "memory");
}
__device__ __forceinline__ void st_w1(unsigned long long* p, uint32_t v, uint32_t tag, bool on) {
    unsigned long long w = ((unsigned long long)tag << 32) | v;
    asm volatile("{\n.reg .pred p;\nsetp.ne.u32 p, %2, 0;\n@p st.relaxed.gpu.global.b64 [%0], %1;\n}" ::"l"(p), "l"(w), "r"((uint32_t)on) : "memory");
}
__device__ __forceinline__ void st_w2(unsigned long long* p, uint32_t v0, uint32_t v1, uint32_t tag, bool on) {
    unsigned long long w0 = ((unsigned long long)tag << 32) | v0, w1 = ((unsigned long long)tag << 32) | v1;
    asm volatile("{\n.reg .pred p;\nsetp.ne.u32 p, %3, 0;\n@p st.relaxed.gpu.global.v2.b64 [%0], {%1, %2};\n}"
                 ::"l"(p), "l"(w0), "l"(w1), "r"((uint32_t)on) : "memory");
}
template <int N, bool ATOM>
__device__ __forceinline__ void poll2(const unsigned long long* p, const int (&off)[N], uint32_t (&v)[2 * N], uint32_t tag, bool on) {
    unsigned long long w[2 * N];
    uint32_t need[N];
#pragma unroll
    for (int i = 0; i < N; i++) { w[2 * i] = w[2 * i + 1] = (unsigned long long)tag << 32; need[i] = on; }
    unsigned n = 0;
    while (true) {
#pragma unroll
        for (int i = 0; i < N; i++) rd16<ATOM>(w[2 * i], w[2 * i + 1], p + off[i], need[i]);
        uint32_t any = 0;
#pragma unroll
        for (int i = 0; i < N; i++) {
            need[i] = ((uint32_t)(w[2 * i] >> 32) ^ tag) | ((uint32_t)(w[2 * i + 1] >> 32) ^ tag);
            any |= need[i];
        }
        if (!__any_sync(0xffffffffu, any != 0)) break;
        __nanosleep(SLEEP_NS);
        if (++n > SPIN_LIMIT) __trap();
    }
#pragma unroll
    for (int i = 0; i < 2 * N; i++) v[i] = (uint32_t)w[i];
}
__device__ __forceinline__ uint32_t tagf(float v, uint32_t tg) { return (fu(v) & ~3u) | tg; }
__device__ __forceinline__ void st_t1(uint32_t* p, uint32_t v) {
    asm volatile("st.relaxed.gpu.global.b32 [%0], %1;" ::"l"(p), "r"(v) : "memory");
}
__device__ __forceinline__ void st_t4(uint32_t* p, uint32_t a, uint32_t b, uint32_t c, uint32_t d) {
    asm volatile("st.relaxed.gpu.global.v4.b32 [%0], {%1, %2, %3, %4};" ::"l"(p), "r"(a), "r"(b), "r"(c), "r"(d) : "memory");
}
template <int N, int STRIDE, bool ATOM>
__device__ __forceinline__ void poll_lines(const uint32_t* p, float (&v)[N], uint32_t tg) {
    uint32_t w[N];
#pragma unroll
    for (int i = 0; i < N; i++) w[i] = 0;
    unsigned n = 0;
    while (true) {
#pragma unroll
        for (int i = 0; i < N; i++) {
            if (ATOM)
                asm volatile("{\n.reg .pred p;\nsetp.ne.u32 p, %2, 0;\n@p atom.relaxed.gpu.global.or.b32 %0, [%1], 0;\n}"
                             : "+r"(w[i]) : "l"(p + i * STRIDE), "r"((w[i] ^ tg) & 3u) : "memory");
            else
                asm volatile("{\n.reg .pred p;\nsetp.ne.u32 p, %2, 0;\n@p ld.relaxed.gpu.global.b32 %0, [%1];\n}"
                             : "+r"(w[i]) : "l"(p + i * STRIDE), "r"((w[i] ^ tg) & 3u) : "memory");
        }
        uint32_t any = 0;
#pragma unroll
        for (int i = 0; i < N; i++) any |= w[i] ^ tg;
        if (!__any_sync(0xffffffffu, (any & 3u) != 0)) break;
        if (++n > SPIN_LIMIT) __trap();
    }
#pragma unroll
    for (int i = 0; i < N; i++) v[i] = uf(w[i] & ~3u);
}
__device__ __forceinline__ void announce(unsigned int* c, bool on) {
    if (on) asm volatile("red.relaxed.gpu.global.add.u32 [%0], 1;" ::"l"(c) : "memory");
}
template <bool SLEEP>
__device__ __forceinline__ void await_count(const unsigned int* p, unsigned target, uint32_t gate, int lane) {
    unsigned n = 0, c;
    while (true) {
        c = 0;
        if (lane == 0) asm volatile("atom.relaxed.gpu.global.or.b32 %0, [%1], 0;" : "=r"(c) : "l"(p) : "memory");
        c = __shfl_sync(0xffffffffu, c, 0);
        if (c >= target) break;
        if (SLEEP) __nanosleep(SLEEP_NS);
        if (++n > SPIN_LIMIT) __trap();
    }
    mbar_arrive_if(gate, 1, lane == 0);
}

__device__ __forceinline__ float rbf(float x) {
    uint32_t r;
    asm("cvt.rn.bf16x2.f32 %0, %1, 0f00000000;" : "=r"(r) : "f"(x));
    return uf(r);
}
__device__ __forceinline__ uint32_t pack2(float lo, float hi) {
    __nv_bfloat162 v = __floats2bfloat162_rn(lo, hi);
    return *reinterpret_cast<uint32_t*>(&v);
}
__device__ __forceinline__ float bf_lo(uint32_t v) { return uf(v << 16); }
__device__ __forceinline__ float bf_hi(uint32_t v) { return uf(v & 0xffff0000u); }
__device__ __forceinline__ float bf_sel(uint32_t v, int hi) { return hi ? bf_hi(v) : bf_lo(v); }
__device__ __forceinline__ float sel4(int t, float a, float b, float c, float d) {
    return (t & 2) ? ((t & 1) ? d : c) : ((t & 1) ? b : a);
}

__device__ __forceinline__ void ln_part1(const float (&v)[4], uint32_t stats, int warp, int lane) {
    float mean = 0.25f * ((v[0] + v[1]) + (v[2] + v[3]));
    float m2;
    { float a = v[0] - mean, b = v[1] - mean, c = v[2] - mean, d = v[3] - mean; m2 = (a * a + b * b) + (c * c + d * d); }
    float cnt_half = 2.f;
#pragma unroll
    for (int s = 0; s < 4; s++) {
        const int mask = (s == 0) ? 1 : (s == 1) ? 2 : (s == 2) ? 8 : 16;
        const float om = __shfl_xor_sync(0xffffffffu, mean, mask);
        const float o2 = __shfl_xor_sync(0xffffffffu, m2, mask);
        const float d = om - mean;
        m2 = (m2 + o2) + d * d * cnt_half;
        mean = 0.5f * (mean + om);
        cnt_half *= 2.f;
    }
    sts64_if(stats + ((lane >> 2) & 1) * 80 + warp * 8, fu(mean), fu(m2), (lane & ~4) == 0);
}
__device__ __forceinline__ void ln_part2(float (&v)[4], uint32_t stats, int lane) {
    const uint32_t st = stats + ((lane >> 2) & 1) * 80;
    const float4 a = lds_f4(st), b = lds_f4(st + 16), c = lds_f4(st + 32), d = lds_f4(st + 48);
    const float2 e = lds_f2(st + 64);
    const float mu = ((((a.x + a.z) + (b.x + b.z)) + ((c.x + c.z) + (d.x + d.z))) + e.x) * (1.f / 9.f);
    const float M2 = (((a.y + a.w) + (b.y + b.w)) + ((c.y + c.w) + (d.y + d.w))) + e.y;
    const float q0 = a.x - mu, q1 = a.z - mu, q2 = b.x - mu, q3 = b.z - mu, q4 = c.x - mu, q5 = c.z - mu, q6 = d.x - mu,
                q7 = d.z - mu, q8 = e.x - mu;
    const float dd = (((q0 * q0 + q1 * q1) + (q2 * q2 + q3 * q3)) + ((q4 * q4 + q5 * q5) + (q6 * q6 + q7 * q7))) + q8 * q8;
    const float mb = rbf(mu);
    const float vb = rbf((M2 + 64.f * dd) * (1.f / 576.f));
    float sq, rd;
    asm("sqrt.approx.f32 %0, %1;" : "=f"(sq) : "f"(rbf(vb + 1e-5f)));
    asm("rcp.approx.f32 %0, %1;" : "=f"(rd) : "f"(rbf(sq)));
#pragma unroll
    for (int i = 0; i < 4; i++) v[i] = rbf(rbf(v[i] - mb) * rd);
}

__device__ __forceinline__ void spread_b(uint32_t (&b)[4][2], uint32_t r0, uint32_t r1, int lane) {
#pragma unroll
    for (int ks = 0; ks < 4; ks++) {
        const int src = (ks << 3) | (lane & 7);
        b[ks][0] = __shfl_sync(0xffffffffu, r0, src);
        b[ks][1] = __shfl_sync(0xffffffffu, r1, src);
    }
}

__device__ __noinline__ void gemv32(uint32_t tile, uint32_t bar, uint32_t r0, uint32_t r1, uint32_t red, int warp) {
    const int lane = threadIdx.x & 31;
    uint32_t b[4][2];
    spread_b(b, r0, r1, lane);
    float acc[2][4] = {};
    const int rr = (lane & 7) + ((lane >> 4) << 3);
    const uint32_t a0 = tile + (warp * 64 + rr) * 64;
    const int sw = (rr >> 1) & 3, c = (lane >> 3) & 1;
    mbar_wait(bar + 8 * (warp / 3));
#pragma unroll
    for (int ks = 0; ks < 4; ks++) {
#pragma unroll
        for (int mt = 0; mt < 2; mt++) {
            uint32_t a[4];
            ldsm4t(a, a0 + ks * 1024 + (((mt * 2 + c) ^ sw) << 4));
            mma(acc[mt], a, b[ks][0], b[ks][1]);
        }
    }
    const int t = lane & 3, g = lane >> 2;
    sts64_if(red + (warp * 32 + t * 8 + g) * 8, fu(sel4(t, acc[0][0], acc[0][2], acc[1][0], acc[1][2])),
             fu(sel4(t, acc[0][1], acc[0][3], acc[1][1], acc[1][3])), true);
}
__device__ __forceinline__ float2 sum9(uint32_t red) {
    float2 v[9];
#pragma unroll
    for (int w = 0; w < 9; w++) v[w] = lds_f2(red + w * 256);
    return make_float2((((v[0].x + v[1].x) + (v[2].x + v[3].x)) + ((v[4].x + v[5].x) + (v[6].x + v[7].x))) + v[8].x,
                       (((v[0].y + v[1].y) + (v[2].y + v[3].y)) + ((v[4].y + v[5].y) + (v[6].y + v[7].y))) + v[8].y);
}

__device__ __forceinline__ void reduce_part1(const uint32_t* p, uint32_t r2, int warp, int lane, uint32_t tg) {
    float v[16];
    poll_lines<16, DM * 2, false>(p, v, tg);
    const float s = (((v[0] + v[1]) + (v[2] + v[3])) + ((v[4] + v[5]) + (v[6] + v[7]))) +
                    (((v[8] + v[9]) + (v[10] + v[11])) + ((v[12] + v[13]) + (v[14] + v[15])));
    sts32_if(r2 + (warp * 32 + (lane >> 2) + (lane & 2) * 4 + (lane & 1) * 16) * 4, fu(s), true);
}
__device__ __forceinline__ float reduce_part2(uint32_t r2, int lane) {
    float a[8];
#pragma unroll
    for (int w = 0; w < 8; w++) a[w] = lds_f(r2 + (w * 32 + lane) * 4);
    return ((a[0] + a[1]) + (a[2] + a[3])) + ((a[4] + a[5]) + (a[6] + a[7]));
}
__device__ __forceinline__ uint32_t next_epoch(const Scratch* gs) {
    uint32_t e;
    asm volatile("ld.relaxed.gpu.global.u32 %0, [%1];" : "=r"(e) : "l"(&gs->epoch) : "memory");
    return e >= 0x7ffffffeu ? 1u : e + 1;
}

__global__ void __launch_bounds__(NTHR, 1)
fused_block_kernel(const __nv_bfloat16* __restrict__ x, const __nv_bfloat16* __restrict__ cvec, __nv_bfloat16* __restrict__ out,
                   Scratch* __restrict__ gs, const char* __restrict__ kbytes, const __grid_constant__ Params mp)
{
    extern __shared__ __align__(1024) unsigned char smem_raw[];
    const uint32_t base = ((uint32_t)__cvta_generic_to_shared(smem_raw) + 1023u) & ~1023u;
    const uint32_t bars = base + OFF_BAR;
    uint32_t t_start = now_ns();
    const bool helper = blockIdx.x < NHELP;
    const int cta = helper ? NCTA + blockIdx.x : blockIdx.x - NHELP;
    const bool heavy = cta >= 96;
    const int mblk0 = helper ? 96 + 3 * blockIdx.x : cta;
    const int krow = ((((cta >> 2) & 1) * 16 + (cta >> 3)) * SK + (SK - WIN)) + (cta & 3) * 64;

    if (threadIdx.x >= 320) {
        const int lane = threadIdx.x & 31, warp = __shfl_sync(0xffffffffu, threadIdx.x >> 5, 0);
        const int nops = helper ? NOPS_HELP : heavy ? NOPS_HEAVY : NOPS_LIGHT;
        const int npre = helper ? 3 : 3 + K_AT_START;
        uint4 tab0 = make_uint4(0, 0, 0, 0), tab1 = tab0;
        {
            const uint4* ops = mp.op + (helper ? NOPS_LIGHT + NOPS_HEAVY : heavy ? NOPS_LIGHT : 0);
            const int i0 = npre + (warp & 1) + 2 * lane;
            if (i0 < nops) asm volatile("ld.v4.u32 {%0,%1,%2,%3}, [%4];" : "=r"(tab0.x), "=r"(tab0.y), "=r"(tab0.z), "=r"(tab0.w) : "l"(ops + i0));
            if (i0 + 64 < nops) asm volatile("ld.v4.u32 {%0,%1,%2,%3}, [%4];" : "=r"(tab1.x), "=r"(tab1.y), "=r"(tab1.z), "=r"(tab1.w) : "l"(ops + i0 + 64));
        }
        if (warp == 10 && lane >= 1 && lane < M_COUNT) asm volatile("prefetch.tensormap [%0];" ::"l"(&mp.m[lane]) : "memory");
        const int xcol = 4096 + (cta - 96) * 16;
        const int base0 = helper ? (mblk0 + lane - 1) * 32 : lane == 1 ? cta * 32 : lane == 2 ? xcol : 0;
        const int base1 = lane == 1 ? krow : lane == 4 ? cta * 288 : lane == 5 ? xcol * 9 : 0;
        uint64_t pol;
        asm volatile("createpolicy.fractional.L2::evict_first.b64 %0, 1.0;" : "=l"(pol));
        const int cnt = (nops - npre + 1 - (warp & 1)) >> 1;
        asm volatile("bar.sync 3, 384;" ::: "memory");
#pragma unroll 1
        for (int k = 0; k < cnt; k++) {
            if (k == 32) tab0 = tab1;
            uint4 e;
            e.x = __shfl_sync(0xffffffffu, tab0.x, k); e.y = __shfl_sync(0xffffffffu, tab0.y, k);
            e.z = __shfl_sync(0xffffffffu, tab0.z, k); e.w = __shfl_sync(0xffffffffu, tab0.w, k);
            const uint32_t bar = bars + (e.x >> 24) * 8;
            const int c0 = __shfl_sync(0xffffffffu, base0, (e.x >> 10) & 3);
            const int c1 = (e.y & 0xfff) + __shfl_sync(0xffffffffu, base1, (e.x >> 12) & 7);
            const uint32_t dst = base + (e.x & 0x3ff) * 256;
            const CUtensorMap* map = &mp.m[(e.x >> 15) & 15];
            mbar_wait(bars + ((e.y >> 12) & 0xff) * 8);
            if (lane == 0) mbar_expect(bar, ((e.x >> 19) & 15) << 10);
            if (e.x & (1u << 23)) {
                const int lag = (int)(now_ns() - (t_start + (e.y >> 20) * 16)) + ANCHOR_BIAS;
                if (lag > 0) t_start += lag;
            }
            const uint32_t due = t_start + (e.y >> 20) * 16;
            unsigned n = 0;
            while (true) {
                const int lvl = min(max(PACE_MID + ((int)(now_ns() - due) >> PACE_SHIFT), 0), 7);
                if (mbar_test(bars + (__byte_perm(e.z, e.w, lvl) & 0xff) * 8)) break;
                if (++n > 64 * SPIN_LIMIT) __trap();
            }
            if (lane == 0) tma3d_hint(dst, map, c0, c1, bar, pol);
            __syncwarp();
        }
        return;
    }

    if (threadIdx.x == 32 && !helper) {
#pragma unroll
        for (int i = 0; i < K_AT_START; i++) mbar_init(bars + 8 * (U_KV + i), 1);
        mbar_init_fence();
#pragma unroll
        for (int i = 0; i < K_AT_START; i++) {
            mbar_expect(bars + 8 * (U_KV + i), CH);
            asm volatile("cp.async.bulk.shared::cluster.global.mbarrier::complete_tx::bytes [%0], [%1], %2, [%3];"
                         ::"r"(base + (S0 + i) * CH), "l"(kbytes + (size_t)krow * 256 + i * CH), "r"(CH), "r"(bars + 8 * (U_KV + i)) : "memory");
        }
    }
    if (threadIdx.x == 0) {
        const bool q1 = heavy && !helper;
        const uint32_t bb = bars + (q1 ? 8 * U_WQ : 0), dst = base + (q1 ? OFF_WQ : OFF_WMOD);
#pragma unroll
        for (int i = 0; i < 3; i++) { mbar_init(bars + 8 * i, 1); mbar_init(bars + 8 * (U_WQ + i), 1); }
        mbar_init_fence();
#pragma unroll
        for (int i = 0; i < 3; i++) {
            mbar_expect(bb + 8 * i, 12288);
            tma3d(dst + i * 12288, &mp.m[q1 ? M_WQ : M_WMOD], mblk0 * 32, i * 192, bb + 8 * i);
        }
    }
    int tid;
    asm volatile("mov.u32 %0, %tid.x;" : "=r"(tid));
    const int lane = tid & 31;
    const int warp = __shfl_sync(0xffffffffu, tid >> 5, 0);
    if (elect_one()) {
        if (warp < 7) {
            const uint32_t b0 = bars + warp * 128;
            if (warp != 0 && warp != 5) {
#pragma unroll
                for (int i = 0; i < 3; i++) mbar_init(b0 + 8 * i, 1);
            }
            if (warp != 6) {
#pragma unroll
                for (int i = 6; i < 16; i++) mbar_init(b0 + 8 * i, 1);
            }
#pragma unroll
            for (int i = 3; i < 6; i++)
                if (i >= 3 + K_AT_START || warp != 0 || helper) mbar_init(b0 + 8 * i, 1);
            mbar_arrive_if(bars + 8 * B_DONE, 1, warp == 5);
        }
        if (warp >= 6) {
#pragma unroll
            for (int i = 0; i < 16; i++) mbar_init(bars + 8 * (B_USED + (warp - 6) * 16 + i), 8);
        }
        mbar_init_fence();
    }
    __syncwarp();
    asm volatile("bar.arrive 3, 384;\nbar.sync 8, 320;" ::: "memory");

    if (warp == 9) {
        if (helper) return;
        const uint32_t ep = next_epoch(gs);
        unsigned int (*cnt)[RCNT][32] = gs->cnt[ep % 3];
        if (cta < C_COUNT && lane < RCNT) st_t1(&gs->cnt[(ep + 1) % 3][cta][lane][0], 0u);
        await_count<true>(cnt[C_MOD][cta % RCNT], HINT_MOD, bars + 8 * B_GATE_MOD, lane);
        mbar_wait(bars + 8 * (U_KV + 63));
        {
            float v[8];
            poll_lines<8, 256, true>(gs->ex_o + (cta & ~7) * 256 + (cta & 7) * 32 + lane, v, 1 + ep % 3);
            const float o0 = (v[0] + v[1]) + (v[2] + v[3]), o1 = (v[4] + v[5]) + (v[6] + v[7]);
            const float r = __shfl_xor_sync(0xffffffffu, (lane & 1) ? o0 : o1, 1);
            const int wi = lane >> 1;
            sts32_if(base + OFF_OB + ((lane & 1) * 16 + (wi & 3) * 4 + (wi >> 2)) * 4, (lane & 1) ? pack2(r, o1) : pack2(o0, r), true);
        }
        asm volatile("bar.arrive 4, 320;" ::: "memory");
        if (cta < NRED) await_count<false>(cnt[C_AO][cta % RCNT0], HINT_AO, bars + 8 * B_GATE_AO, lane);
        await_count<false>(cnt[C_X1][cta % RCNT], HINT_X1, bars + 8 * B_GATE_X1, lane);
        asm volatile("bar.sync 6, 320;" ::: "memory");
#pragma unroll
        for (int h = 0; h < 2; h++) {
            if (h == 0 || heavy) {
                const int ci = h * 32 + (h ? lane & 15 : lane);
                float4 u[9];
#pragma unroll
                for (int w = 0; w < 9; w++) u[w] = lds_f4(base + OFF_SC + (w * 48 + ci) * 16);
                float4 s;
                s.x = (((u[0].x + u[1].x) + (u[2].x + u[3].x)) + ((u[4].x + u[5].x) + (u[6].x + u[7].x))) + u[8].x;
                s.y = (((u[0].y + u[1].y) + (u[2].y + u[3].y)) + ((u[4].y + u[5].y) + (u[6].y + u[7].y))) + u[8].y;
                s.z = (((u[0].z + u[1].z) + (u[2].z + u[3].z)) + ((u[4].z + u[5].z) + (u[6].z + u[7].z))) + u[8].z;
                s.w = (((u[0].w + u[1].w) + (u[2].w + u[3].w)) + ((u[4].w + u[5].w) + (u[6].w + u[7].w))) + u[8].w;
                float g0 = rbf(s.x), g1 = rbf(s.y);
                g0 = g0 * (g0 > 0.f ? 1.f : 0.f);
                g1 = g1 * (g1 > 0.f ? 1.f : 0.f);
                const uint32_t hp = pack2(g0 * rbf(s.z), g1 * rbf(s.w));
                sts16(base + OFF_HH + ci * 2, hp);
                sts16(base + OFF_HH + 128 + ci * 2, hp >> 16);
            }
        }
        asm volatile("bar.arrive 7, 320;" ::: "memory");
        return;
    }

    const int kvh = cta >> 3, bat = (cta >> 2) & 1;
    const int nmod = helper ? 3 : heavy ? 0 : 1;
    const int g = lane >> 2, t = lane & 3;
    const int fb = g & 1;
    const int col0 = warp * 64 + (g >> 1) * 16 + 2 * t;
    const bool reducer = cta < NRED;
    const int rcol = (reducer ? cta : 0) * 16 + (lane & 15), rb_ = lane >> 4;
    const uint32_t s_sc = base + OFF_SC, s_stats = base + OFF_ST, s_r2 = base + OFF_R2;
    const uint32_t ca_ = ldg32(cvec + fb * DM + col0), cb_ = ldg32(cvec + fb * DM + col0 + 8);
    const uint32_t xa = ldg32(x + fb * DM + col0), xb = ldg32(x + fb * DM + col0 + 8);
    const uint32_t tag = next_epoch(gs);
    const float xr = bf_sel(ldg32(x + rb_ * DM + (rcol & ~1)), lane & 1);
    unsigned int (*cnt)[RCNT][32] = gs->cnt[tag % 3];

    float y[4] = {bf_lo(xa), bf_hi(xa), bf_lo(xb), bf_hi(xb)};
    {
        float cv[4] = {bf_lo(ca_), bf_hi(ca_), bf_lo(cb_), bf_hi(cb_)};
#pragma unroll
        for (int i = 0; i < 4; i++) cv[i] = cv[i] / (1.f + expf(-cv[i]));
        const uint32_t s01 = pack2(cv[0], cv[1]), s23 = pack2(cv[2], cv[3]);
        ln_part1(y, s_stats, warp, lane);
#pragma unroll 1
        for (int m = 0; m < nmod; m++)
            gemv32(base + OFF_WMOD + m * 36864, bars + 8 * (m == 1 ? U_WQ : m == 2 ? 3 : 0), s01, s23, s_sc + m * 2304, warp);
    }
    bar_comp();
    if (warp < nmod) {
        const float2 s2 = sum9(s_sc + warp * 2304 + lane * 8);
#pragma unroll
        for (int r = 0; r < REP1; r++) st_w1(gs->ex_mod + r * 6 * DM + (mblk0 + warp) * 32 + lane, pack2(s2.x, s2.y), tag, true);
        announce(cnt[C_MOD][lane & (RCNT - 1)], cta < 36 && lane < RCNT);
    }
    if (helper) return;
    mbar_arrive_if(bars + 8 * B_MODFREE, 1, tid == 256);
    ln_part2(y, s_stats, lane);
    const int rr = (lane & 7) + ((lane >> 4) << 3), hi8 = (lane >> 3) & 1;
    float cbv[4], sbv[4], gar, gbr;
    const int zoff[1] = {0};
    {
        const unsigned long long* mod = gs->ex_mod + (cta % REP1) * 6 * DM;
        const int moff[4] = {0, 8, DM, DM + 8};
        uint32_t v[8];
        mbar_wait(bars + 8 * B_GATE_MOD);
        poll2<4, false>(mod + col0, moff, v, tag, true);
        float h[4];
#pragma unroll
        for (int i = 0; i < 4; i++) h[i] = rbf(y[i] * rbf(1.f + bf_sel(v[4 + i], fb))) + bf_sel(v[i], fb);
        gemv32(base + OFF_WQ, bars + 8 * U_WQ, pack2(h[0], h[1]), pack2(h[2], h[3]), s_sc + 2304, warp);
        bar_comp();
        if (warp == 0) {
            const float2 s2 = sum9(s_sc + 2304 + lane * 8);
            const float o0 = __shfl_xor_sync(0xffffffffu, s2.x, 1), o1 = __shfl_xor_sync(0xffffffffu, s2.y, 1);
            st_w1(gs->ex_q + (lane & 1) * 2048 + cta * 16 + (lane >> 1), (lane & 1) ? pack2(o1, s2.y) : pack2(s2.x, o0), tag, true);
        }
        mbar_arrive_if(bars + 8 * B_WQFREE, 1, tid == 256);
        poll2<4, false>(mod + 3 * DM + col0, moff, v, tag, true);
#pragma unroll
        for (int i = 0; i < 4; i++) { sbv[i] = bf_sel(v[i], fb); cbv[i] = rbf(1.f + bf_sel(v[4 + i], fb)); }
        if (warp < 2) {
            uint32_t qv[2];
            poll2<1, true>(gs->ex_q + bat * 2048 + kvh * 128 + tid * 2, zoff, qv, tag, true);
            sts64_if(base + OFF_Q + tid * 8, qv[0], qv[1], true);
        }
        bar_comp();
        const int goff[2] = {0, 3 * DM};
        uint32_t gv[4];
        poll2<2, false>(mod + 2 * DM + (rcol & ~1), goff, gv, tag, reducer && warp == RED_WARP);
        gar = bf_sel((lane & 1) ? gv[1] : gv[0], rb_);
        gbr = bf_sel((lane & 1) ? gv[3] : gv[2], rb_);
    }

    const int line0 = rr * 9 + warp;
    const uint32_t rowa = base + line0 * 128;
    const uint32_t lsw = line0 & 7;
    uint32_t wf[4][4][4];
    const uint32_t tg0 = 1 + tag % 3, tg1 = 1 + (2 * (tag % 3)) % 3, tg2 = 1 + (2 * (tag % 3) + 1) % 3;
    unsigned long long* x1dst = gs->ex_x1 + ((lane >> 3) & 1) * 288 + cta * 8 + rb_ * 4 + ((lane >> 1) & 3);
    uint32_t* part = gs->ex_part + cta * (DM * 2) + (warp * 4 + t) * 32 + g * 4;
    const bool x1pub = reducer && warp == RED_WARP && (lane & 1) == 0;
    auto prewrite = [&]() { st_t4(part, 0u, 0u, 0u, 0u); st_w1(x1dst, 0u, 0u, x1pub); };
    auto publish = [&](const float (&acc)[4][4], uint32_t tg) {
        st_t4(part, tagf(sel4(t, acc[0][0], acc[1][0], acc[2][0], acc[3][0]), tg), tagf(sel4(t, acc[0][1], acc[1][1], acc[2][1], acc[3][1]), tg),
              tagf(sel4(t, acc[0][2], acc[1][2], acc[2][2], acc[3][2]), tg), tagf(sel4(t, acc[0][3], acc[1][3], acc[2][3], acc[3][3]), tg));
    };

    if (warp < 8) {
        uint4 qf[4];
#pragma unroll
        for (int j = 0; j < 4; j++) qf[j] = lds128(base + OFF_Q + (g & 1) * 256 + ((j ^ ((g >> 1) & 1)) << 6) + t * 16);
        float mx0 = -INFINITY, mx1 = -INFINITY;
        const uint32_t rowoff = base + ((warp & 1) * 16 + g) * 256 + t * 16;
        const uint32_t sw = (g & 1) << 6;
        const bool valid = (g & 1) == (t & 1);
        uint32_t scp = s_sc + (warp * 16 + g + ((t & 2) << 2)) * 4;
#pragma unroll 1
        for (int c = warp >> 1; c < 32; c += 4) {
            const int s = c + S0 >= NS ? c + S0 - NS : c + S0;
            mbar_wait(bars + 8 * (U_KV + c));
            const uint32_t a0 = rowoff + s * CH;
            float acc[4] = {}, acc2[4] = {};
#pragma unroll
            for (int j = 0; j < 4; j++) {
                const uint32_t o = (j << 6) ^ sw;
                const uint4 lo = lds128(a0 + o), hi = lds128(a0 + 2048 + o);
                mma(acc, lo.x, hi.x, lo.y, hi.y, qf[j].x, qf[j].y);
                mma(acc2, lo.z, hi.z, lo.w, hi.w, qf[j].z, qf[j].w);
            }
            __syncwarp();
            mbar_arrive_if(bars + 8 * (B_USED + c), 4, lane == 0);
            float u0 = (t & 2) ? acc[2] + acc2[2] : acc[0] + acc2[0];
            float u1 = (t & 2) ? acc[3] + acc2[3] : acc[1] + acc2[1];
            u0 = rbf(rbf(u0) * 0.08838834764831845f);
            u1 = rbf(rbf(u1) * 0.08838834764831845f);
            sts32_if(scp, fu(u0), valid);
            sts32_if(scp + 4096, fu(u1), valid);
            mx0 = valid ? fmaxf(mx0, u0) : mx0;
            mx1 = valid ? fmaxf(mx1, u1) : mx1;
            scp += 512;
        }
#pragma unroll
        for (int m = 1; m < 32; m <<= 1) {
            mx0 = fmaxf(mx0, __shfl_xor_sync(0xffffffffu, mx0, m));
            mx1 = fmaxf(mx1, __shfl_xor_sync(0xffffffffu, mx1, m));
        }
        sts64_if(s_stats + warp * 8, fu(mx0), fu(mx1), lane == 0);
        bar_256();
        const int uh = g & 1;
        float mloc = -INFINITY;
#pragma unroll
        for (int w = 0; w < 8; w++) mloc = fmaxf(mloc, lds_f(s_stats + (2 * w + uh) * 4));
        float e[8];
#pragma unroll
        for (int i = 0; i < 4; i++) {
            const float2 v = lds_f2(s_sc + (uh * 1024 + (tid >> 3) * 32 + 2 * t + i * 8) * 4);
            e[2 * i] = __expf(v.x - mloc);
            e[2 * i + 1] = __expf(v.y - mloc);
        }
        float l = ((e[0] + e[1]) + (e[2] + e[3])) + ((e[4] + e[5]) + (e[6] + e[7]));
        l += __shfl_xor_sync(0xffffffffu, l, 1);
        l += __shfl_xor_sync(0xffffffffu, l, 2);
        l += __shfl_xor_sync(0xffffffffu, l, 8);
        l += __shfl_xor_sync(0xffffffffu, l, 16);
        sts32_if(s_stats + (16 + 2 * warp + uh) * 4, fu(l), (lane & ~4) == 0);
        bar_256();
        if (warp == 0) {
            float lt = 0.f;
#pragma unroll
            for (int w = 0; w < 8; w++) lt += lds_f(s_stats + (16 + 2 * w + uh) * 4);
            st_w2(gs->ex_ml + cta * 4 + uh * 2, fu(mloc), fu(lt), tag, (lane & ~4) == 0);
            uint32_t ml[2];
            poll2<1, true>(gs->ex_ml + ((cta & ~3) + t) * 4 + uh * 2, zoff, ml, tag, true);
            const float ms = uf(ml[0]), ls = uf(ml[1]);
            float M = fmaxf(ms, __shfl_xor_sync(0xffffffffu, ms, 1));
            M = fmaxf(M, __shfl_xor_sync(0xffffffffu, M, 2));
            float L = ls * __expf(ms - M);
            L += __shfl_xor_sync(0xffffffffu, L, 1);
            L += __shfl_xor_sync(0xffffffffu, L, 2);
            sts32_if(s_stats + (32 + uh) * 4, fu(__expf(mloc - M) / L), (lane & ~4) == 0);
        }
        bar_256();
        const float f = lds_f(s_stats + (32 + uh) * 4);
        sts128_if(base + OFF_P + tid * 16, pack2(e[0] * f, e[1] * f), pack2(e[2] * f, e[3] * f), pack2(e[4] * f, e[5] * f),
                  pack2(e[6] * f, e[7] * f), true);
        bar_256();

        float acc[4] = {}, acc2[4] = {};
        const int cc = (warp & 3) * 2 + hi8;
        const uint32_t voff = base + (warp >> 2) * (CH / 2) + rr * 128 + ((cc ^ (lane & 7)) << 4);
        uint32_t poff = base + OFF_P + (g & 1) * 64 + t * 16;
        uint32_t* odst = gs->ex_o + cta * 256 + (t & 1) * 128 + warp * 16 + ((t & 2) << 2) + g;
#pragma unroll 1
        for (int c = 32; c < 64; c++) {
            const int s = c + S0 >= 2 * NS ? c + S0 - 2 * NS : c + S0 - NS;
            if (c == PREWRITE_AT) { st_t1(odst, 0u); prewrite(); }
            const uint4 p0 = lds128(poff);
            poff += 128;
            mbar_wait(bars + 8 * (U_KV + c));
            uint32_t a[4], a2[4];
            ldsm4t(a, voff + s * CH);
            ldsm4t(a2, voff + s * CH + 2048);
            mma(acc, a, p0.x, p0.y);
            mma(acc2, a2, p0.z, p0.w);
            __syncwarp();
            mbar_arrive_if(bars + 8 * (B_USED + c), 1, lane == 0);
        }
        st_t1(odst, tagf(sel4(t, acc[0] + acc2[0], acc[1] + acc2[1], acc[2] + acc2[2], acc[3] + acc2[3]), tg0));
    } else {
        mbar_wait(bars + 8 * (U_KV + PREWRITE_AT));
        prewrite();
    }
    {
#pragma unroll
        for (int ks = 0; ks < 2; ks++) {
            mbar_wait(bars + 8 * (U_WO + 2 * ks)); mbar_wait(bars + 8 * (U_WO + 2 * ks + 1));
#pragma unroll
            for (int mt = 0; mt < 4; mt++) ldsm4t(wf[ks][mt], rowa + OFF_WO + ks * 18432 + (((mt * 2 + hi8) ^ lsw) << 4));
        }
        asm volatile("bar.sync 4, 320;" ::: "memory");
        const uint4 ob = lds128(base + OFF_OB + fb * 64 + t * 16);
        float acc[4][4] = {};
#pragma unroll
        for (int mt = 0; mt < 4; mt++) mma(acc[mt], wf[0][mt], ob.x, ob.y);
#pragma unroll
        for (int mt = 0; mt < 4; mt++) mma(acc[mt], wf[1][mt], ob.z, ob.w);
        publish(acc, tg1);
        announce(cnt[C_AO][lane & (RCNT - 1)], warp == 8 && lane < RCNT0);
    }
    const uint32_t gub = bars + 8 * (U_GU + 2 * (warp / 3));
    const uint32_t gxb = heavy ? bars + 8 * (U_GX + 2 * (warp / 3)) : gub;
    uint32_t dn[3][4][4];
    auto load_gu = [&]() {
        const uint32_t rb = base + OFF_GU + hi8 * 36864 + (warp * 64 + rr) * 64;
#pragma unroll
        for (int ks = 0; ks < 4; ks++)
#pragma unroll
            for (int j = 0; j < 4; j++) ldsm4t(wf[ks][j], rb + ks * 1024 + ((j ^ ((rr >> 1) & 3)) << 4));
        if (heavy) {
            const uint32_t rx = base + OFF_GX + hi8 * 18432 + (warp * 64 + rr) * 32;
#pragma unroll
            for (int ks = 0; ks < 4; ks++)
#pragma unroll
                for (int j = 0; j < 2; j++) ldsm4t(dn[1 + j][ks], rx + ks * 512 + ((j ^ ((rr >> 2) & 1)) << 4));
        }
    };
    auto load_dn = [&](int ks) {
#pragma unroll
        for (int mt = 0; mt < 4; mt++) ldsm4t(dn[ks][mt], rowa + OFF_DN + ks * 18432 + (((mt * 2 + hi8) ^ lsw) << 4));
    };
    auto dn_in = [&](int ks) {
        return __all_sync(0xffffffffu, mbar_test(bars + 8 * (U_DN + 2 * ks)) && mbar_test(bars + 8 * (U_DN + 2 * ks + 1)));
    };
    bool have_gu = false, have_dn = false;
    auto try_gu = [&]() {
        if (!have_gu && __all_sync(0xffffffffu, mbar_test(gxb + 8) && mbar_test(gxb) && mbar_test(gub + 8) && mbar_test(gub))) {
            load_gu();
            have_gu = true;
        }
    };
    auto gate = [&](uint32_t gb) {
        unsigned n = 0;
        while (true) {
            try_gu();
            if (__all_sync(0xffffffffu, have_gu ? mbar_try(gb) : mbar_test(gb))) break;
            if (++n > 64 * SPIN_LIMIT) __trap();
        }
    };
    const uint32_t* rsrc = gs->ex_part + (warp & 7) * 16 * (DM * 2) + cta * 32 + lane;
    float x1r = 0.f;
    if (reducer) {
        gate(bars + 8 * B_GATE_AO);
        if (warp < 8) reduce_part1(rsrc, s_r2, warp, lane, tg1);
        bar_comp();
        if (warp == RED_WARP) {
            x1r = rbf(xr + rbf(gar * rbf(reduce_part2(s_r2, lane))));
            const float other = __shfl_xor_sync(0xffffffffu, x1r, 1);
            st_w1(x1dst, pack2(x1r, other), tag, x1pub);
            announce(cnt[C_X1][lane & (RCNT - 1)], lane < RCNT);
        }
    }
    gate(bars + 8 * B_GATE_X1);
    {
        unsigned long long w0, w1;
        unsigned n = 0;
        while (true) {
            asm volatile("ld.relaxed.gpu.global.b64 %0, [%1];" : "=l"(w0) : "l"(gs->ex_x1 + tid) : "memory");
            asm volatile("ld.relaxed.gpu.global.b64 %0, [%1];" : "=l"(w1) : "l"(gs->ex_x1 + 288 + tid) : "memory");
            try_gu();
            if (!have_dn && dn_in(0)) { load_dn(0); have_dn = true; }
            if (__all_sync(0xffffffffu, (uint32_t)(w0 >> 32) == tag && (uint32_t)(w1 >> 32) == tag)) break;
            if (++n > SPIN_LIMIT) __trap();
        }
        y[0] = bf_lo((uint32_t)w0); y[1] = bf_hi((uint32_t)w0); y[2] = bf_lo((uint32_t)w1); y[3] = bf_hi((uint32_t)w1);
        ln_part1(y, s_stats, warp, lane);
        if (!have_gu) { mbar_wait(gub); mbar_wait(gub + 8); mbar_wait(gxb); mbar_wait(gxb + 8); load_gu(); }
        bar_comp();
        ln_part2(y, s_stats, lane);
        uint32_t bfr[4][2];
        spread_b(bfr, pack2(rbf(y[0] * cbv[0]) + sbv[0], rbf(y[1] * cbv[1]) + sbv[1]),
                 pack2(rbf(y[2] * cbv[2]) + sbv[2], rbf(y[3] * cbv[3]) + sbv[3]), lane);
        const uint32_t red = s_sc + (warp * 48 + g + t * 8) * 16;
        float acc[4][4] = {};
#pragma unroll
        for (int ks = 0; ks < 4; ks++)
#pragma unroll
            for (int j = 0; j < 4; j++) mma(acc[j], wf[ks][j], bfr[ks][0], bfr[ks][1]);
        if (heavy) {
            float ax[2][4] = {};
#pragma unroll
            for (int ks = 0; ks < 4; ks++)
#pragma unroll
                for (int j = 0; j < 2; j++) mma(ax[j], dn[1 + j][ks], bfr[ks][0], bfr[ks][1]);
            sts128_if(red + 512, fu(t ? ax[1][0] : ax[0][0]), fu(t ? ax[1][1] : ax[0][1]), fu(t ? ax[1][2] : ax[0][2]),
                      fu(t ? ax[1][3] : ax[0][3]), t < 2);
        }
        sts128_if(red, fu(sel4(t, acc[0][0], acc[1][0], acc[2][0], acc[3][0])), fu(sel4(t, acc[0][1], acc[1][1], acc[2][1], acc[3][1])),
                  fu(sel4(t, acc[0][2], acc[1][2], acc[2][2], acc[3][2])), fu(sel4(t, acc[0][3], acc[1][3], acc[2][3], acc[3][3])), true);
        asm volatile("bar.arrive 6, 320;" ::: "memory");
    }
    {
        bool got[3];
#pragma unroll
        for (int ks = 0; ks < 3; ks++) {
            got[ks] = ks == 0 && have_dn;
            if (!got[ks] && (ks < 2 || heavy) && dn_in(ks)) { load_dn(ks); got[ks] = true; }
        }
        asm volatile("bar.sync 7, 320;" ::: "memory");
        uint32_t hb[6];
#pragma unroll
        for (int i = 0; i < 6; i++) hb[i] = fu(lds_f(base + OFF_HH + (fb * 32 + t + i * 4) * 4));
        float acc[4][4] = {};
#pragma unroll
        for (int ks = 0; ks < 3; ks++) {
            if (ks < 2 || heavy) {
                if (!got[ks]) {
                    mbar_wait(bars + 8 * (U_DN + 2 * ks)); mbar_wait(bars + 8 * (U_DN + 2 * ks + 1));
                    load_dn(ks);
                }
#pragma unroll
                for (int mt = 0; mt < 4; mt++) mma(acc[mt], dn[ks][mt], hb[2 * ks], hb[2 * ks + 1]);
            }
        }
        publish(acc, tg2);
    }
    if (reducer) {
        if (warp < 8) reduce_part1(rsrc, s_r2, warp, lane, tg2);
        bar_comp();
        if (warp == RED_WARP) {
            const float r = x1r + rbf(gbr * rbf(reduce_part2(s_r2, lane)));
            const float other = __shfl_xor_sync(0xffffffffu, r, 1);
            if (x1pub) *reinterpret_cast<uint32_t*>(out + rb_ * DM + rcol) = pack2(r, other);
            if (cta == 0 && lane == 0) st_t1(&gs->epoch, tag);
        }
    }
}

typedef CUresult (*EncodeFn)(CUtensorMap*, CUtensorMapDataType, cuuint32_t, void*, const cuuint64_t*, const cuuint64_t*,
                             const cuuint32_t*, const cuuint32_t*, CUtensorMapInterleave, CUtensorMapSwizzle,
                             CUtensorMapL2promotion, CUtensorMapFloatOOBfill);

void make_map(EncodeFn enc, CUtensorMap* m, const void* p, uint64_t cols, uint64_t rows, uint32_t bc, uint32_t br,
              CUtensorMapSwizzle sw, CUtensorMapL2promotion prom, bool split_halves = false) {
    cuuint64_t gd[3] = {split_halves ? cols / 2 : cols, rows, split_halves ? 2u : 1u};
    cuuint64_t gs[2] = {cols * 2, split_halves ? cols : cols * 2 * rows};
    cuuint32_t bx[3] = {bc, br, split_halves ? 2u : 1u};
    cuuint32_t es[3] = {1, 1, 1};
    enc(m, CU_TENSOR_MAP_DATA_TYPE_BFLOAT16, 3, const_cast<void*>(p), gd, gs, bx, es, CU_TENSOR_MAP_INTERLEAVE_NONE, sw, prom,
        CU_TENSOR_MAP_FLOAT_OOB_FILL_NONE);
}

void build_ops(uint4* op, bool heavy) {
    constexpr int NMAX = NOPS_HEAVY;
    int order[NMAX], n = 0;
    for (int u = 0; u < 3; u++) order[n++] = heavy ? U_WQ + u : u;
    for (int u = U_KV; u < U_KV + K_AT_START; u++) order[n++] = u;
    if (!heavy) for (int u = 0; u < 3; u++) order[n++] = U_WQ + u;
    for (int u = U_KV + K_AT_START; u < U_WO; u++) order[n++] = u;
    const int n_v = n;
    for (int k = 0; k < 4; k++) order[n++] = U_WO + k;
    for (int k = 0; k < 3; k++) {
        order[n++] = U_GU + 2 * k; order[n++] = U_GU + 2 * k + 1;
        if (heavy) { order[n++] = U_GX + 2 * k; order[n++] = U_GX + 2 * k + 1; }
    }
    for (int k = 0; k < (heavy ? 6 : 4); k++) order[n++] = U_DN + k;
    int kb[NMAX], win[NMAX], cum[NMAX + 1];
    cum[0] = 0;
    for (int i = 0; i < n; i++) {
        const int u = order[i];
        int dst, sel0 = 0, sel1 = 0, row = 0, map, spb = -1;
        win[i] = WIN_TAIL;
        if (u < U_KV || (u >= U_WQ && u < U_GX)) {
            const int k = u < U_KV ? u : u - U_WQ + 3;
            map = k < 3 ? M_WMOD : M_WQ; dst = OFF_WMOD + k * 12288; sel0 = 1; row = (k % 3) * 192; kb[i] = 12;
            spb = B_DONE; win[i] = WIN_MID;
        } else if (u < U_WO) {
            const int c = u - U_KV, slot = (c + S0) % NS;
            map = c < 32 ? M_K : M_V; dst = slot * CH; sel1 = 1; row = ((c & 31) >> 1) * 256 + (c & 1) * 32; kb[i] = 8;
            spb = c >= NS ? B_USED + c - NS : (slot >= 9 && slot <= 13) ? B_WQFREE : (slot >= 5 && slot < 9) ? B_MODFREE : B_DONE;
            win[i] = c < 64 - END_CHUNKS ? WIN_MID : WIN_END;
        } else if (u < U_GU) {
            const int k = u - U_WO;
            map = M_WO; dst = OFF_WO + k * 9216; sel1 = 4; row = k * 72; kb[i] = 9; win[i] = WIN_END;
        } else if (u < U_WQ) {
            const int k = u - U_GU;
            map = M_GATE + (k & 1); dst = OFF_GU + (k & 1) * 36864 + (k >> 1) * 12288; sel0 = 1; row = (k >> 1) * 192; kb[i] = 12;
        } else if (u < U_DN) {
            const int k = u - U_GX;
            map = M_GATEX + (k & 1); dst = OFF_GX + (k & 1) * 18432 + (k >> 1) * 6144; sel0 = 2; row = (k >> 1) * 192; kb[i] = 6;
        } else {
            const int k = u - U_DN;
            map = M_DN; dst = OFF_DN + k * 9216; kb[i] = 9; win[i] = WIN_LAST;
            if (k < 4) { sel1 = 4; row = k * 72; } else { sel1 = 5; row = (k - 4) * 72; }
        }
        if (heavy && i >= n_v) win[i] += WIN_HEAVY_EXTRA;
        if (spb < 0) spb = B_USED + 64 - NS + ((dst + kb[i] * 1024 - 1) >> 13);
        cum[i + 1] = cum[i] + kb[i];
        op[i].x = (dst >> 8) | (sel0 << 10) | (sel1 << 12) | (map << 15) | (kb[i] << 19) | ((unsigned)u << 24) |
                  ((i == n_v - ANCHOR_BACK || i == n_v - ANCHOR_BACK + 1) ? 1u << 23 : 0u);
        op[i].y = row | (spb << 12);
    }
    const double tv = heavy ? PACE_TV_HEAVY : PACE_TV;
    for (int i = 0; i < n; i++) {
        double due = i <= n_v ? PACE_T0 + (tv - PACE_T0) * cum[i] / cum[n_v] : tv + (PACE_TE - tv) * (cum[i] - cum[n_v]) / (cum[n] - cum[n_v]);
        if (due < 0) due = 0;
        op[i].y |= (unsigned)(due / 16) << 20;
        unsigned long long lv = 0;
        for (int l = 0; l < 8; l++) {
            int w = win[i] + (l - PACE_MID) * PACE_STEP, wd = B_DONE;
            if (w < PACE_WMIN) w = PACE_WMIN;
            if (w > PACE_WMAX) w = PACE_WMAX;
            if (i >= n_v && w > win[i] + TAIL_UP) w = win[i] + TAIL_UP;
            for (int j = i - 1; j >= 0; j--)
                if (cum[i + 1] - cum[j] > w) { wd = order[j]; break; }
            lv |= (unsigned long long)wd << (8 * l);
        }
        op[i].z = (unsigned)lv;
        op[i].w = (unsigned)(lv >> 32);
    }
}

}

extern "C" void kernel_launch(void* const* d_in, const int* in_sizes, int n_in, void* d_out, int out_size) {
    (void)in_sizes; (void)n_in; (void)out_size;
    const __nv_bfloat16* x = (const __nv_bfloat16*)d_in[0];
    const __nv_bfloat16* kc = (const __nv_bfloat16*)d_in[1];
    const __nv_bfloat16* vc = (const __nv_bfloat16*)d_in[2];
    const __nv_bfloat16* wq = (const __nv_bfloat16*)d_in[3];
    const __nv_bfloat16* wo = (const __nv_bfloat16*)d_in[4];
    const __nv_bfloat16* wg = (const __nv_bfloat16*)d_in[6];
    const __nv_bfloat16* wu = (const __nv_bfloat16*)d_in[7];
    const __nv_bfloat16* wd = (const __nv_bfloat16*)d_in[8];
    const __nv_bfloat16* cv = (const __nv_bfloat16*)d_in[9];
    const __nv_bfloat16* wm = (const __nv_bfloat16*)d_in[10];

    EncodeFn enc = nullptr;
    cudaDriverEntryPointQueryResult qr;
    cudaGetDriverEntryPoint("cuTensorMapEncodeTiled", (void**)&enc, cudaEnableDefault, &qr);
    cudaFuncSetAttribute(fused_block_kernel, cudaFuncAttributeMaxDynamicSharedMemorySize, SMEM_BYTES);
    Params mp;
    const CUtensorMapL2promotion P128 = CU_TENSOR_MAP_L2_PROMOTION_L2_128B, P256 = CU_TENSOR_MAP_L2_PROMOTION_L2_256B;
    make_map(enc, &mp.m[M_WMOD], wm, 6 * DM, DM, 32, 192, CU_TENSOR_MAP_SWIZZLE_64B, P128);
    make_map(enc, &mp.m[M_WQ], wq, 4096, DM, 32, 192, CU_TENSOR_MAP_SWIZZLE_64B, P128);
    make_map(enc, &mp.m[M_K], kc, 128, (uint64_t)2 * 16 * SK, 128, 32, CU_TENSOR_MAP_SWIZZLE_NONE, P256);
    make_map(enc, &mp.m[M_V], vc, 128, (uint64_t)2 * 16 * SK, 64, 32, CU_TENSOR_MAP_SWIZZLE_128B, P256, true);
    make_map(enc, &mp.m[M_WO], wo, 64, 4096 * 9, 64, 72, CU_TENSOR_MAP_SWIZZLE_128B, P256);
    make_map(enc, &mp.m[M_DN], wd, 64, FF * 9, 64, 72, CU_TENSOR_MAP_SWIZZLE_128B, P256);
    make_map(enc, &mp.m[M_GATE], wg, FF, DM, 32, 192, CU_TENSOR_MAP_SWIZZLE_64B, P128);
    make_map(enc, &mp.m[M_UP], wu, FF, DM, 32, 192, CU_TENSOR_MAP_SWIZZLE_64B, P128);
    make_map(enc, &mp.m[M_GATEX], wg, FF, DM, 16, 192, CU_TENSOR_MAP_SWIZZLE_32B, P128);
    make_map(enc, &mp.m[M_UPX], wu, FF, DM, 16, 192, CU_TENSOR_MAP_SWIZZLE_32B, P128);
    build_ops(mp.op, false);
    build_ops(mp.op + NOPS_LIGHT, true);
    for (int i = 0; i < NOPS_HELP; i++) {
        const int blk = i / 3, bar = (blk == 0 ? 0 : blk == 1 ? U_WQ : 3) + i % 3;
        mp.op[NOPS_LIGHT + NOPS_HEAVY + i] =
            make_uint4(((OFF_WMOD + i * 12288) >> 8) | ((blk + 1) << 10) | (M_WMOD << 15) | (12 << 19) | (bar << 24),
                       (i % 3) * 192 | (B_DONE << 12), B_DONE * 0x01010101u, B_DONE * 0x01010101u);
    }
    Scratch* gs = nullptr;
    cudaGetSymbolAddress((void**)&gs, g_scratch);
    fused_block_kernel<<<NCTA + NHELP, NTHR, SMEM_BYTES>>>(x, cv, (__nv_bfloat16*)d_out, gs, (const char*)kc, mp);
}
```

```cpp
#include <cuda_runtime.h>
#include <cuda.h>
#include <cuda_bf16.h>
#include <stdint.h>

namespace {

constexpr int DM = 576;
constexpr int FF = 4608;
constexpr int SK = 32768;
constexpr int WIN = 4096;
constexpr int NCTA = 128;
constexpr int NHELP = 4;
constexpr int NTHR = 384;
constexpr int NRED = 36;
constexpr int RED_WARP = 8;

constexpr int WIN_MID = 40, WIN_END = 48, WIN_TAIL = 32, WIN_LAST = 36;
constexpr int WIN_HEAVY_EXTRA = 12, END_CHUNKS = 8;
constexpr int PACE_T0 = -500, PACE_TV = 23100, PACE_TV_HEAVY = 22900, PACE_TE = 29600;
constexpr int PACE_MID = 3, PACE_STEP = 8, PACE_SHIFT = 8;
constexpr int PACE_WMIN = 18, PACE_WMAX = 64, TAIL_UP = 8;
constexpr int ANCHOR_BACK = 8, ANCHOR_BIAS = 650;
constexpr int K_AT_START = 2;
constexpr int REP1 = 8;
constexpr int RCNT = 8, RCNT0 = 4;
constexpr unsigned HINT_MOD = 36, HINT_AO = 112, HINT_X1 = 28;
constexpr int PREWRITE_AT = 54;
constexpr int SLEEP_NS = 100;
constexpr unsigned SPIN_LIMIT = 1u << 22;

constexpr int CH = 8192;
constexpr int NS = 26;
constexpr int S0 = 14;
constexpr int OFF_WMOD = 40960;
constexpr int OFF_WQ = 77824;
constexpr int OFF_WO = 0;
constexpr int OFF_GU = 36864;
constexpr int OFF_GX = 110592;
constexpr int OFF_DN = 147456;
constexpr int OFF_SC = NS * CH;
constexpr int OFF_P = OFF_SC + 8192;
constexpr int OFF_Q = OFF_P + 4096;
constexpr int OFF_ST = OFF_Q + 512;
constexpr int OFF_HH = OFF_ST + 256;
constexpr int OFF_R2 = OFF_HH + 256;
constexpr int OFF_OB = OFF_R2 + 1024;
constexpr int OFF_BAR = OFF_OB + 128;
constexpr int SMEM_BYTES = OFF_BAR + 192 * 8 + 1024;
static_assert(SMEM_BYTES <= 232448, "smem");

constexpr int U_KV = 3;
constexpr int U_WO = 67;
constexpr int U_GU = 71;
constexpr int U_WQ = 80;
constexpr int U_GX = 83;
constexpr int U_DN = 89;
constexpr int B_DONE = 95;
constexpr int B_MODFREE = 96, B_WQFREE = 97;
constexpr int B_GATE_AO = 98, B_GATE_X1 = 99, B_GATE_MOD = 100;
constexpr int B_USED = 128;

enum { M_WMOD, M_WQ, M_K, M_V, M_WO, M_DN, M_GATE, M_UP, M_GATEX, M_UPX, M_COUNT };
constexpr int NPRE = 3 + K_AT_START;
constexpr int NOPS_LIGHT = 84 - NPRE, NOPS_HEAVY = 89 - NPRE, NOPS_HELP = 6;
struct Params { CUtensorMap m[M_COUNT]; uint4 op[NOPS_LIGHT + NOPS_HEAVY + NOPS_HELP]; };

enum { C_AO, C_X1, C_SPARE, C_MOD, C_COUNT };
static_assert(sizeof(Params) + 64 <= 4096, "kernel parameters");
struct __align__(128) Scratch {
    unsigned int epoch;
    unsigned int pad[31];
    unsigned int cnt[3][C_COUNT][RCNT][32];
    unsigned long long ex_mod[REP1 * 6 * DM];
    unsigned long long ex_q[2 * 2048];
    unsigned long long ex_x1[DM];
    unsigned long long ex_ml[NCTA * 4];
    uint32_t ex_o[NCTA * 256];
    uint32_t ex_part[NCTA * DM * 2];
};
__device__ Scratch g_scratch;

__device__ __forceinline__ uint32_t fu(float x) { return __float_as_uint(x); }
__device__ __forceinline__ float uf(uint32_t x) { return __uint_as_float(x); }
__device__ __forceinline__ uint32_t now_ns() { uint32_t t; asm volatile("mov.u32 %0, %globaltimer_lo;" : "=r"(t)); return t; }
__device__ __forceinline__ void mbar_init(uint32_t b, int c) {
    asm volatile("mbarrier.init.shared::cta.b64 [%0], %1;" ::"r"(b), "r"(c) : "memory");
}
__device__ __forceinline__ void mbar_init_fence() { asm volatile("fence.mbarrier_init.release.cluster;" ::: "memory"); }
__device__ __forceinline__ void mbar_expect(uint32_t b, uint32_t bytes) {
    asm volatile("mbarrier.arrive.expect_tx.shared::cta.b64 _, [%0], %1;" ::"r"(b), "r"(bytes) : "memory");
}
__device__ __forceinline__ void mbar_arrive_if(uint32_t b, uint32_t cnt, bool p) {
    asm volatile("{\n.reg .pred p;\nsetp.ne.u32 p, %2, 0;\n@p mbarrier.arrive.shared::cta.b64 _, [%0], %1;\n}"
                 ::"r"(b), "r"(cnt), "r"((uint32_t)p) : "memory");
}
__device__ __forceinline__ bool mbar_try(uint32_t b) {
    uint32_t ok;
    asm volatile("{\n.reg .pred p;\nmbarrier.try_wait.parity.shared::cta.b64 p, [%1], 0;\nselp.u32 %0, 1, 0, p;\n}"
                 : "=r"(ok) : "r"(b) : "memory");
    return ok;
}
__device__ __forceinline__ bool mbar_test(uint32_t b) {
    uint32_t ok;
    asm volatile("{\n.reg .pred p;\nmbarrier.test_wait.parity.shared::cta.b64 p, [%1], 0;\nselp.u32 %0, 1, 0, p;\n}"
                 : "=r"(ok) : "r"(b) : "memory");
    return ok;
}
__device__ __forceinline__ void mbar_wait(uint32_t b) {
    unsigned n = 0;
    while (!mbar_try(b))
        if (++n > SPIN_LIMIT) __trap();
}
__device__ __forceinline__ void tma3d(uint32_t dst, const CUtensorMap* m, int c0, int c1, uint32_t bar) {
    asm volatile("cp.async.bulk.tensor.3d.shared::cluster.global.mbarrier::complete_tx::bytes [%0], [%1, {%3, %4, %5}], [%2];"
                 ::"r"(dst), "l"(m), "r"(bar), "r"(c0), "r"(c1), "r"(0) : "memory");
}
__device__ __forceinline__ void tma3d_hint(uint32_t dst, const CUtensorMap* m, int c0, int c1, uint32_t bar, uint64_t pol) {
    asm volatile("cp.async.bulk.tensor.3d.shared::cluster.global.mbarrier::complete_tx::bytes.L2::cache_hint [%0], [%1, {%3, %4, %5}], [%2], %6;"
                 ::"r"(dst), "l"(m), "r"(bar), "r"(c0), "r"(c1), "r"(0), "l"(pol) : "memory");
}
__device__ __forceinline__ bool elect_one() {
    uint32_t p;
    asm volatile("{\n.reg .pred p;\nelect.sync _|p, 0xffffffff;\nselp.u32 %0, 1, 0, p;\n}" : "=r"(p));
    return p;
}
__device__ __forceinline__ uint32_t ldg32(const void* p) {
    uint32_t v;
    asm volatile("ld.global.nc.u32 %0, [%1];" : "=r"(v) : "l"(p));
    return v;
}
__device__ __forceinline__ void bar_comp() { asm volatile("bar.sync 1, 288;" ::: "memory"); }
__device__ __forceinline__ void bar_256() { asm volatile("bar.sync 2, 256;" ::: "memory"); }
__device__ __forceinline__ void sts16(uint32_t a, uint32_t v) { asm volatile("st.shared.b16 [%0], %1;" ::"r"(a), "h"((unsigned short)v) : "memory"); }
__device__ __forceinline__ void sts32_if(uint32_t a, uint32_t v, bool p) {
    asm volatile("{\n.reg .pred p;\nsetp.ne.u32 p, %2, 0;\n@p st.shared.b32 [%0], %1;\n}" ::"r"(a), "r"(v), "r"((uint32_t)p) : "memory");
}
__device__ __forceinline__ void sts64_if(uint32_t a, uint32_t v0, uint32_t v1, bool p) {
    asm volatile("{\n.reg .pred p;\nsetp.ne.u32 p, %3, 0;\n@p st.shared.v2.b32 [%0], {%1, %2};\n}" ::"r"(a), "r"(v0), "r"(v1), "r"((uint32_t)p) : "memory");
}
__device__ __forceinline__ void sts128_if(uint32_t a, uint32_t v0, uint32_t v1, uint32_t v2, uint32_t v3, bool p) {
    asm volatile("{\n.reg .pred p;\nsetp.ne.u32 p, %5, 0;\n@p st.shared.v4.b32 [%0], {%1, %2, %3, %4};\n}"
                 ::"r"(a), "r"(v0), "r"(v1), "r"(v2), "r"(v3), "r"((uint32_t)p) : "memory");
}
__device__ __forceinline__ float lds_f(uint32_t a) { float v; asm volatile("ld.shared.f32 %0, [%1];" : "=f"(v) : "r"(a) : "memory"); return v; }
__device__ __forceinline__ float2 lds_f2(uint32_t a) {
    float2 v; asm volatile("ld.shared.v2.f32 {%0,%1}, [%2];" : "=f"(v.x), "=f"(v.y) : "r"(a) : "memory"); return v;
}
__device__ __forceinline__ float4 lds_f4(uint32_t a) {
    float4 v; asm volatile("ld.shared.v4.f32 {%0,%1,%2,%3}, [%4];" : "=f"(v.x), "=f"(v.y), "=f"(v.z), "=f"(v.w) : "r"(a) : "memory"); return v;
}
__device__ __forceinline__ uint4 lds128(uint32_t addr) {
    uint4 v;
    asm volatile("ld.shared.v4.u32 {%0,%1,%2,%3}, [%4];" : "=r"(v.x), "=r"(v.y), "=r"(v.z), "=r"(v.w) : "r"(addr) : "memory");
    return v;
}
__device__ __forceinline__ void ldsm4t(uint32_t (&a)[4], uint32_t addr) {
    asm volatile("ldmatrix.sync.aligned.m8n8.x4.trans.shared.b16 {%0,%1,%2,%3}, [%4];"
                 : "=r"(a[0]), "=r"(a[1]), "=r"(a[2]), "=r"(a[3]) : "r"(addr) : "memory");
}
__device__ __forceinline__ void mma(float (&c)[4], uint32_t a0, uint32_t a1, uint32_t a2, uint32_t a3, uint32_t b0, uint32_t b1) {
    asm volatile("mma.sync.aligned.m16n8k16.row.col.f32.bf16.bf16.f32 {%0,%1,%2,%3}, {%4,%5,%6,%7}, {%8,%9}, {%0,%1,%2,%3};"
                 : "+f"(c[0]), "+f"(c[1]), "+f"(c[2]), "+f"(c[3])
                 : "r"(a0), "r"(a1), "r"(a2), "r"(a3), "r"(b0), "r"(b1));
}
__device__ __forceinline__ void mma(float (&c)[4], const uint32_t (&a)[4], uint32_t b0, uint32_t b1) {
    mma(c, a[0], a[1], a[2], a[3], b0, b1);
}

template <bool ATOM>
__device__ __forceinline__ void rd16(unsigned long long& a, unsigned long long& b, const void* p, uint32_t on) {
    if (ATOM)
        asm volatile("{\n.reg .pred p;\n.reg .b128 z, d;\nsetp.ne.u32 p, %3, 0;\nmov.b128 z, {0, 0};\nmov.b128 d, {%0, %1};\n"
                     "@p atom.relaxed.gpu.global.cas.b128 d, [%2], z, z;\nmov.b128 {%0, %1}, d;\n}"
                     : "+l"(a), "+l"(b) : "l"(p), "r"(on) : "memory");
    else
        asm volatile("{\n.reg .pred p;\nsetp.ne.u32 p, %3, 0;\n@p ld.relaxed.gpu.global.v2.b64 {%0, %1}, [%2];\n}"
                     : "+l"(a), "+l"(b) : "l"(p), "r"(on) : "memory");
}
__device__ __forceinline__ void st_w1(unsigned long long* p, uint32_t v, uint32_t tag, bool on) {
    unsigned long long w = ((unsigned long long)tag << 32) | v;
    asm volatile("{\n.reg .pred p;\nsetp.ne.u32 p, %2, 0;\n@p st.relaxed.gpu.global.b64 [%0], %1;\n}" ::"l"(p), "l"(w), "r"((uint32_t)on) : "memory");
}
__device__ __forceinline__ void st_w2(unsigned long long* p, uint32_t v0, uint32_t v1, uint32_t tag, bool on) {
    unsigned long long w0 = ((unsigned long long)tag << 32) | v0, w1 = ((unsigned long long)tag << 32) | v1;
    asm volatile("{\n.reg .pred p;\nsetp.ne.u32 p, %3, 0;\n@p st.relaxed.gpu.global.v2.b64 [%0], {%1, %2};\n}"
                 ::"l"(p), "l"(w0), "l"(w1), "r"((uint32_t)on) : "memory");
}
template <int N, bool ATOM>
__device__ __forceinline__ void poll2(const unsigned long long* p, const int (&off)[N], uint32_t (&v)[2 * N], uint32_t tag, bool on) {
    unsigned long long w[2 * N];
    uint32_t need[N];
#pragma unroll
    for (int i = 0; i < N; i++) { w[2 * i] = w[2 * i + 1] = (unsigned long long)tag << 32; need[i] = on; }
    unsigned n = 0;
    while (true) {
#pragma unroll
        for (int i = 0; i < N; i++) rd16<ATOM>(w[2 * i], w[2 * i + 1], p + off[i], need[i]);
        uint32_t any = 0;
#pragma unroll
        for (int i = 0; i < N; i++) {
            need[i] = ((uint32_t)(w[2 * i] >> 32) ^ tag) | ((uint32_t)(w[2 * i + 1] >> 32) ^ tag);
            any |= need[i];
        }
        if (!__any_sync(0xffffffffu, any != 0)) break;
        __nanosleep(SLEEP_NS);
        if (++n > SPIN_LIMIT) __trap();
    }
#pragma unroll
    for (int i = 0; i < 2 * N; i++) v[i] = (uint32_t)w[i];
}
__device__ __forceinline__ uint32_t tagf(float v, uint32_t tg) { return (fu(v) & ~3u) | tg; }
__device__ __forceinline__ void st_t1(uint32_t* p, uint32_t v) {
    asm volatile("st.relaxed.gpu.global.b32 [%0], %1;" ::"l"(p), "r"(v) : "memory");
}
__device__ __forceinline__ void st_t4(uint32_t* p, uint32_t a, uint32_t b, uint32_t c, uint32_t d) {
    asm volatile("st.relaxed.gpu.global.v4.b32 [%0], {%1, %2, %3, %4};" ::"l"(p), "r"(a), "r"(b), "r"(c), "r"(d) : "memory");
}
template <int N, int STRIDE, bool ATOM>
__device__ __forceinline__ void poll_lines(const uint32_t* p, float (&v)[N], uint32_t tg) {
    uint32_t w[N];
#pragma unroll
    for (int i = 0; i < N; i++) w[i] = 0;
    unsigned n = 0;
    while (true) {
#pragma unroll
        for (int i = 0; i < N; i++) {
            if (ATOM)
                asm volatile("{\n.reg .pred p;\nsetp.ne.u32 p, %2, 0;\n@p atom.relaxed.gpu.global.or.b32 %0, [%1], 0;\n}"
                             : "+r"(w[i]) : "l"(p + i * STRIDE), "r"((w[i] ^ tg) & 3u) : "memory");
            else
                asm volatile("{\n.reg .pred p;\nsetp.ne.u32 p, %2, 0;\n@p ld.relaxed.gpu.global.b32 %0, [%1];\n}"
                             : "+r"(w[i]) : "l"(p + i * STRIDE), "r"((w[i] ^ tg) & 3u) : "memory");
        }
        uint32_t any = 0;
#pragma unroll
        for (int i = 0; i < N; i++) any |= w[i] ^ tg;
        if (!__any_sync(0xffffffffu, (any & 3u) != 0)) break;
        if (++n > SPIN_LIMIT) __trap();
    }
#pragma unroll
    for (int i = 0; i < N; i++) v[i] = uf(w[i] & ~3u);
}
__device__ __forceinline__ void announce(unsigned int* c, bool on) {
    if (on) asm volatile("red.relaxed.gpu.global.add.u32 [%0], 1;" ::"l"(c) : "memory");
}
template <bool SLEEP>
__device__ __forceinline__ void await_count(const unsigned int* p, unsigned target, uint32_t gate, int lane) {
    unsigned n = 0, c;
    while (true) {
        c = 0;
        if (lane == 0) asm volatile("atom.relaxed.gpu.global.or.b32 %0, [%1], 0;" : "=r"(c) : "l"(p) : "memory");
        c = __shfl_sync(0xffffffffu, c, 0);
        if (c >= target) break;
        if (SLEEP) __nanosleep(SLEEP_NS);
        if (++n > SPIN_LIMIT) __trap();
    }
    mbar_arrive_if(gate, 1, lane == 0);
}

__device__ __forceinline__ float rbf(float x) {
    uint32_t r;
    asm("cvt.rn.bf16x2.f32 %0, %1, 0f00000000;" : "=r"(r) : "f"(x));
    return uf(r);
}
__device__ __forceinline__ uint32_t pack2(float lo, float hi) {
    __nv_bfloat162 v = __floats2bfloat162_rn(lo, hi);
    return *reinterpret_cast<uint32_t*>(&v);
}
__device__ __forceinline__ float bf_lo(uint32_t v) { return uf(v << 16); }
__device__ __forceinline__ float bf_hi(uint32_t v) { return uf(v & 0xffff0000u); }
__device__ __forceinline__ float bf_sel(uint32_t v, int hi) { return hi ? bf_hi(v) : bf_lo(v); }
__device__ __forceinline__ float sel4(int t, float a, float b, float c, float d) {
    return (t & 2) ? ((t & 1) ? d : c) : ((t & 1) ? b : a);
}

__device__ __forceinline__ void ln_part1(const float (&v)[4], uint32_t stats, int warp, int lane) {
    float mean = 0.25f * ((v[0] + v[1]) + (v[2] + v[3]));
    float m2;
    { float a = v[0] - mean, b = v[1] - mean, c = v[2] - mean, d = v[3] - mean; m2 = (a * a + b * b) + (c * c + d * d); }
    float cnt_half = 2.f;
#pragma unroll
    for (int s = 0; s < 4; s++) {
        const int mask = (s == 0) ? 1 : (s == 1) ? 2 : (s == 2) ? 8 : 16;
        const float om = __shfl_xor_sync(0xffffffffu, mean, mask);
        const float o2 = __shfl_xor_sync(0xffffffffu, m2, mask);
        const float d = om - mean;
        m2 = (m2 + o2) + d * d * cnt_half;
        mean = 0.5f * (mean + om);
        cnt_half *= 2.f;
    }
    sts64_if(stats + ((lane >> 2) & 1) * 80 + warp * 8, fu(mean), fu(m2), (lane & ~4) == 0);
}
__device__ __forceinline__ void ln_part2(float (&v)[4], uint32_t stats, int lane) {
    const uint32_t st = stats + ((lane >> 2) & 1) * 80;
    const float4 a = lds_f4(st), b = lds_f4(st + 16), c = lds_f4(st + 32), d = lds_f4(st + 48);
    const float2 e = lds_f2(st + 64);
    const float mu = ((((a.x + a.z) + (b.x + b.z)) + ((c.x + c.z) + (d.x + d.z))) + e.x) * (1.f / 9.f);
    const float M2 = (((a.y + a.w) + (b.y + b.w)) + ((c.y + c.w) + (d.y + d.w))) + e.y;
    const float q0 = a.x - mu, q1 = a.z - mu, q2 = b.x - mu, q3 = b.z - mu, q4 = c.x - mu, q5 = c.z - mu, q6 = d.x - mu,
                q7 = d.z - mu, q8 = e.x - mu;
    const float dd = (((q0 * q0 + q1 * q1) + (q2 * q2 + q3 * q3)) + ((q4 * q4 + q5 * q5) + (q6 * q6 + q7 * q7))) + q8 * q8;
    const float mb = rbf(mu);
    const float vb = rbf((M2 + 64.f * dd) * (1.f / 576.f));
    float sq, rd;
    asm("sqrt.approx.f32 %0, %1;" : "=f"(sq) : "f"(rbf(vb + 1e-5f)));
    asm("rcp.approx.f32 %0, %1;" : "=f"(rd) : "f"(rbf(sq)));
#pragma unroll
    for (int i = 0; i < 4; i++) v[i] = rbf(rbf(v[i] - mb) * rd);
}

__device__ __forceinline__ void spread_b(uint32_t (&b)[4][2], uint32_t r0, uint32_t r1, int lane) {
#pragma unroll
    for (int ks = 0; ks < 4; ks++) {
        const int src = (ks << 3) | (lane & 7);
        b[ks][0] = __shfl_sync(0xffffffffu, r0, src);
        b[ks][1] = __shfl_sync(0xffffffffu, r1, src);
    }
}

__device__ __noinline__ void gemv32(uint32_t tile, uint32_t bar, uint32_t r0, uint32_t r1, uint32_t red, int warp) {
    const int lane = threadIdx.x & 31;
    uint32_t b[4][2];
    spread_b(b, r0, r1, lane);
    float acc[2][4] = {};
    const int rr = (lane & 7) + ((lane >> 4) << 3);
    const uint32_t a0 = tile + (warp * 64 + rr) * 64;
    const int sw = (rr >> 1) & 3, c = (lane >> 3) & 1;
    mbar_wait(bar + 8 * (warp / 3));
#pragma unroll
    for (int ks = 0; ks < 4; ks++) {
#pragma unroll
        for (int mt = 0; mt < 2; mt++) {
            uint32_t a[4];
            ldsm4t(a, a0 + ks * 1024 + (((mt * 2 + c) ^ sw) << 4));
            mma(acc[mt], a, b[ks][0], b[ks][1]);
        }
    }
    const int t = lane & 3, g = lane >> 2;
    sts64_if(red + (warp * 32 + t * 8 + g) * 8, fu(sel4(t, acc[0][0], acc[0][2], acc[1][0], acc[1][2])),
             fu(sel4(t, acc[0][1], acc[0][3], acc[1][1], acc[1][3])), true);
}
__device__ __forceinline__ float2 sum9(uint32_t red) {
    float2 v[9];
#pragma unroll
    for (int w = 0; w < 9; w++) v[w] = lds_f2(red + w * 256);
    return make_float2((((v[0].x + v[1].x) + (v[2].x + v[3].x)) + ((v[4].x + v[5].x) + (v[6].x + v[7].x))) + v[8].x,
                       (((v[0].y + v[1].y) + (v[2].y + v[3].y)) + ((v[4].y + v[5].y) + (v[6].y + v[7].y))) + v[8].y);
}

__device__ __forceinline__ void reduce_part1(const uint32_t* p, uint32_t r2, int warp, int lane, uint32_t tg) {
    float v[16];
    poll_lines<16, DM * 2, false>(p, v, tg);
    const float s = (((v[0] + v[1]) + (v[2] + v[3])) + ((v[4] + v[5]) + (v[6] + v[7]))) +
                    (((v[8] + v[9]) + (v[10] + v[11])) + ((v[12] + v[13]) + (v[14] + v[15])));
    sts32_if(r2 + (warp * 32 + (lane >> 2) + (lane & 2) * 4 + (lane & 1) * 16) * 4, fu(s), true);
}
__device__ __forceinline__ float reduce_part2(uint32_t r2, int lane) {
    float a[8];
#pragma unroll
    for (int w = 0; w < 8; w++) a[w] = lds_f(r2 + (w * 32 + lane) * 4);
    return ((a[0] + a[1]) + (a[2] + a[3])) + ((a[4] + a[5]) + (a[6] + a[7]));
}
__device__ __forceinline__ uint32_t next_epoch(const Scratch* gs) {
    uint32_t e;
    asm volatile("ld.relaxed.gpu.global.u32 %0, [%1];" : "=r"(e) : "l"(&gs->epoch) : "memory");
    return e >= 0x7ffffffeu ? 1u : e + 1;
}

__global__ void __launch_bounds__(NTHR, 1)
fused_block_kernel(const __nv_bfloat16* __restrict__ x, const __nv_bfloat16* __restrict__ cvec, __nv_bfloat16* __restrict__ out,
                   Scratch* __restrict__ gs, const char* __restrict__ kbytes, const __grid_constant__ Params mp)
{
    extern __shared__ __align__(1024) unsigned char smem_raw[];
    const uint32_t base = ((uint32_t)__cvta_generic_to_shared(smem_raw) + 1023u) & ~1023u;
    const uint32_t bars = base + OFF_BAR;
    const bool helper = blockIdx.x < NHELP;
    const int cta = helper ? NCTA + blockIdx.x : blockIdx.x - NHELP;
    const bool heavy = cta >= 96;
    const int mblk0 = helper ? 96 + 3 * blockIdx.x : cta;
    const int krow = ((((cta >> 2) & 1) * 16 + (cta >> 3)) * SK + (SK - WIN)) + (cta & 3) * 64;
    if (!helper && threadIdx.x < 128)
        asm volatile("prefetch.global.L2 [%0];" ::"l"(kbytes + (size_t)krow * 256 + (threadIdx.x >> 7) * 65536 + (threadIdx.x & 127) * 128));
    uint32_t t_start = now_ns();

    if (threadIdx.x >= 320) {
        const int lane = threadIdx.x & 31, warp = __shfl_sync(0xffffffffu, threadIdx.x >> 5, 0);
        const int nops = helper ? NOPS_HELP : heavy ? NOPS_HEAVY : NOPS_LIGHT;
        uint4 tab0 = make_uint4(0, 0, 0, 0), tab1 = tab0;
        {
            const uint4* ops = mp.op + (helper ? NOPS_LIGHT + NOPS_HEAVY : heavy ? NOPS_LIGHT : 0);
            const int i0 = (warp & 1) + 2 * lane;
            if (i0 < nops) asm volatile("ld.v4.u32 {%0,%1,%2,%3}, [%4];" : "=r"(tab0.x), "=r"(tab0.y), "=r"(tab0.z), "=r"(tab0.w) : "l"(ops + i0));
            if (i0 + 64 < nops) asm volatile("ld.v4.u32 {%0,%1,%2,%3}, [%4];" : "=r"(tab1.x), "=r"(tab1.y), "=r"(tab1.z), "=r"(tab1.w) : "l"(ops + i0 + 64));
        }
        if (warp == 10 && lane >= 1 && lane < M_COUNT) asm volatile("prefetch.tensormap [%0];" ::"l"(&mp.m[lane]) : "memory");
        const int xcol = 4096 + (cta - 96) * 16;
        const int base0 = helper ? (mblk0 + lane - 1) * 32 : lane == 1 ? cta * 32 : lane == 2 ? xcol : 0;
        const int base1 = lane == 1 ? krow : lane == 4 ? cta * 288 : lane == 5 ? xcol * 9 : 0;
        uint64_t pol;
        asm volatile("createpolicy.fractional.L2::evict_first.b64 %0, 1.0;" : "=l"(pol));
        const int cnt = (nops + 1 - (warp & 1)) >> 1;
        asm volatile("bar.sync 3, 384;" ::: "memory");
#pragma unroll 1
        for (int k = 0; k < cnt; k++) {
            if (k == 32) tab0 = tab1;
            uint4 e;
            e.x = __shfl_sync(0xffffffffu, tab0.x, k); e.y = __shfl_sync(0xffffffffu, tab0.y, k);
            e.z = __shfl_sync(0xffffffffu, tab0.z, k); e.w = __shfl_sync(0xffffffffu, tab0.w, k);
            const uint32_t bar = bars + (e.x >> 24) * 8;
            const int c0 = __shfl_sync(0xffffffffu, base0, (e.x >> 10) & 3);
            const int c1 = (e.y & 0xfff) + __shfl_sync(0xffffffffu, base1, (e.x >> 12) & 7);
            const uint32_t dst = base + (e.x & 0x3ff) * 256;
            const CUtensorMap* map = &mp.m[(e.x >> 15) & 15];
            mbar_wait(bars + ((e.y >> 12) & 0xff) * 8);
            if (lane == 0) mbar_expect(bar, ((e.x >> 19) & 15) << 10);
            if (e.x & (1u << 23)) {
                const int lag = (int)(now_ns() - (t_start + (e.y >> 20) * 16)) + ANCHOR_BIAS;
                if (lag > 0) t_start += lag;
            }
            const uint32_t due = t_start + (e.y >> 20) * 16;
            unsigned n = 0;
            while (true) {
                const int lvl = min(max(PACE_MID + ((int)(now_ns() - due) >> PACE_SHIFT), 0), 7);
                if (mbar_test(bars + (__byte_perm(e.z, e.w, lvl) & 0xff) * 8)) break;
                if (++n > 64 * SPIN_LIMIT) __trap();
            }
            if (lane == 0) tma3d_hint(dst, map, c0, c1, bar, pol);
            __syncwarp();
        }
        return;
    }

    if (threadIdx.x == 32 && !helper) {
#pragma unroll
        for (int i = 0; i < K_AT_START; i++) mbar_init(bars + 8 * (U_KV + i), 1);
        mbar_init_fence();
#pragma unroll
        for (int i = 0; i < K_AT_START; i++) {
            mbar_expect(bars + 8 * (U_KV + i), CH);
            asm volatile("cp.async.bulk.shared::cluster.global.mbarrier::complete_tx::bytes [%0], [%1], %2, [%3];"
                         ::"r"(base + (S0 + i) * CH), "l"(kbytes + (size_t)krow * 256 + i * CH), "r"(CH), "r"(bars + 8 * (U_KV + i)) : "memory");
        }
    }
    if (threadIdx.x == 0) {
        const bool q1 = heavy && !helper;
        const uint32_t bb = bars + (q1 ? 8 * U_WQ : 0), dst = base + (q1 ? OFF_WQ : OFF_WMOD);
#pragma unroll
        for (int i = 0; i < 3; i++) { mbar_init(bars + 8 * i, 1); mbar_init(bars + 8 * (U_WQ + i), 1); }
        mbar_init_fence();
#pragma unroll
        for (int i = 0; i < 3; i++) {
            mbar_expect(bb + 8 * i, 12288);
            tma3d(dst + i * 12288, &mp.m[q1 ? M_WQ : M_WMOD], mblk0 * 32, i * 192, bb + 8 * i);
        }
    }
    int tid;
    asm volatile("mov.u32 %0, %tid.x;" : "=r"(tid));
    const int lane = tid & 31;
    const int warp = __shfl_sync(0xffffffffu, tid >> 5, 0);
    if (elect_one()) {
        if (warp < 7) {
            const uint32_t b0 = bars + warp * 128;
            if (warp != 0 && warp != 5) {
#pragma unroll
                for (int i = 0; i < 3; i++) mbar_init(b0 + 8 * i, 1);
            }
            if (warp != 6) {
#pragma unroll
                for (int i = 6; i < 16; i++) mbar_init(b0 + 8 * i, 1);
            }
#pragma unroll
            for (int i = 3; i < 6; i++)
                if (i >= 3 + K_AT_START || warp != 0 || helper) mbar_init(b0 + 8 * i, 1);
            mbar_arrive_if(bars + 8 * B_DONE, 1, warp == 5);
        }
        if (warp >= 6) {
#pragma unroll
            for (int i = 0; i < 16; i++) mbar_init(bars + 8 * (B_USED + (warp - 6) * 16 + i), 8);
        }
        mbar_init_fence();
    }
    __syncwarp();
    asm volatile("bar.arrive 3, 384;\nbar.sync 8, 320;" ::: "memory");

    if (warp == 9) {
        if (helper) return;
        const uint32_t ep = next_epoch(gs);
        unsigned int (*cnt)[RCNT][32] = gs->cnt[ep % 3];
        if (cta < C_COUNT && lane < RCNT) st_t1(&gs->cnt[(ep + 1) % 3][cta][lane][0], 0u);
        await_count<true>(cnt[C_MOD][cta % RCNT], HINT_MOD, bars + 8 * B_GATE_MOD, lane);
        mbar_wait(bars + 8 * (U_KV + 63));
        {
            float v[8];
            poll_lines<8, 256, true>(gs->ex_o + (cta & ~7) * 256 + (cta & 7) * 32 + lane, v, 1 + ep % 3);
            const float o0 = (v[0] + v[1]) + (v[2] + v[3]), o1 = (v[4] + v[5]) + (v[6] + v[7]);
            const float r = __shfl_xor_sync(0xffffffffu, (lane & 1) ? o0 : o1, 1);
            const int wi = lane >> 1;
            sts32_if(base + OFF_OB + ((lane & 1) * 16 + (wi & 3) * 4 + (wi >> 2)) * 4, (lane & 1) ? pack2(r, o1) : pack2(o0, r), true);
        }
        asm volatile("bar.arrive 4, 320;" ::: "memory");
#pragma unroll 1
        for (int k = cta < NRED ? C_AO : C_X1; k <= C_X1; k++)
            await_count<false>(cnt[k][cta % (k ? RCNT : RCNT0)], k ? HINT_X1 : HINT_AO, bars + 8 * (B_GATE_AO + k), lane);
        asm volatile("bar.sync 6, 320;" ::: "memory");
#pragma unroll
        for (int h = 0; h < 2; h++) {
            if (h == 0 || heavy) {
                const int ci = h * 32 + (h ? lane & 15 : lane);
                float4 u[9];
#pragma unroll
                for (int w = 0; w < 9; w++) u[w] = lds_f4(base + OFF_SC + (w * 48 + ci) * 16);
                float4 s;
                s.x = (((u[0].x + u[1].x) + (u[2].x + u[3].x)) + ((u[4].x + u[5].x) + (u[6].x + u[7].x))) + u[8].x;
                s.y = (((u[0].y + u[1].y) + (u[2].y + u[3].y)) + ((u[4].y + u[5].y) + (u[6].y + u[7].y))) + u[8].y;
                s.z = (((u[0].z + u[1].z) + (u[2].z + u[3].z)) + ((u[4].z + u[5].z) + (u[6].z + u[7].z))) + u[8].z;
                s.w = (((u[0].w + u[1].w) + (u[2].w + u[3].w)) + ((u[4].w + u[5].w) + (u[6].w + u[7].w))) + u[8].w;
                float g0 = rbf(s.x), g1 = rbf(s.y);
                g0 = g0 * (g0 > 0.f ? 1.f : 0.f);
                g1 = g1 * (g1 > 0.f ? 1.f : 0.f);
                const uint32_t hp = pack2(g0 * rbf(s.z), g1 * rbf(s.w));
                sts16(base + OFF_HH + ci * 2, hp);
                sts16(base + OFF_HH + 128 + ci * 2, hp >> 16);
            }
        }
        asm volatile("bar.arrive 7, 320;" ::: "memory");
        return;
    }

    const int kvh = cta >> 3, bat = (cta >> 2) & 1;
    const int nmod = helper ? 3 : heavy ? 0 : 1;
    const int g = lane >> 2, t = lane & 3;
    const int fb = g & 1;
    const int col0 = warp * 64 + (g >> 1) * 16 + 2 * t;
    const bool reducer = cta < NRED;
    const int rcol = (reducer ? cta : 0) * 16 + (lane & 15), rb_ = lane >> 4;
    const uint32_t s_sc = base + OFF_SC, s_stats = base + OFF_ST, s_r2 = base + OFF_R2;
    const uint32_t ca_ = ldg32(cvec + fb * DM + col0), cb_ = ldg32(cvec + fb * DM + col0 + 8);
    const uint32_t xa = ldg32(x + fb * DM + col0), xb = ldg32(x + fb * DM + col0 + 8);
    const uint32_t tag = next_epoch(gs);
    const float xr = bf_sel(ldg32(x + rb_ * DM + (rcol & ~1)), lane & 1);
    unsigned int (*cnt)[RCNT][32] = gs->cnt[tag % 3];

    float y[4] = {bf_lo(xa), bf_hi(xa), bf_lo(xb), bf_hi(xb)};
    {
        float cv[4] = {bf_lo(ca_), bf_hi(ca_), bf_lo(cb_), bf_hi(cb_)};
#pragma unroll
        for (int i = 0; i < 4; i++) cv[i] = cv[i] / (1.f + expf(-cv[i]));
        const uint32_t s01 = pack2(cv[0], cv[1]), s23 = pack2(cv[2], cv[3]);
        ln_part1(y, s_stats, warp, lane);
#pragma unroll 1
        for (int m = 0; m < nmod; m++)
            gemv32(base + OFF_WMOD + m * 36864, bars + 8 * (m == 1 ? U_WQ : m == 2 ? 3 : 0), s01, s23, s_sc + m * 2304, warp);
    }
    bar_comp();
    if (warp < nmod) {
        const float2 s2 = sum9(s_sc + warp * 2304 + lane * 8);
#pragma unroll
        for (int r = 0; r < REP1; r++) st_w1(gs->ex_mod + r * 6 * DM + (mblk0 + warp) * 32 + lane, pack2(s2.x, s2.y), tag, true);
        announce(cnt[C_MOD][lane & (RCNT - 1)], cta < 36 && lane < RCNT);
    }
    if (helper) return;
    mbar_arrive_if(bars + 8 * B_MODFREE, 1, tid == 256);
    ln_part2(y, s_stats, lane);
    const int rr = (lane & 7) + ((lane >> 4) << 3), hi8 = (lane >> 3) & 1;
    float cbv[4], sbv[4], gar, gbr;
    const int zoff[1] = {0};
    {
        const unsigned long long* mod = gs->ex_mod + (cta % REP1) * 6 * DM;
        const int moff[4] = {0, 8, DM, DM + 8};
        uint32_t v[8];
        mbar_wait(bars + 8 * B_GATE_MOD);
        poll2<4, false>(mod + col0, moff, v, tag, true);
        float h[4];
#pragma unroll
        for (int i = 0; i < 4; i++) h[i] = rbf(y[i] * rbf(1.f + bf_sel(v[4 + i], fb))) + bf_sel(v[i], fb);
        gemv32(base + OFF_WQ, bars + 8 * U_WQ, pack2(h[0], h[1]), pack2(h[2], h[3]), s_sc + 2304, warp);
        bar_comp();
        if (warp == 0) {
            const float2 s2 = sum9(s_sc + 2304 + lane * 8);
            const float o0 = __shfl_xor_sync(0xffffffffu, s2.x, 1), o1 = __shfl_xor_sync(0xffffffffu, s2.y, 1);
            st_w1(gs->ex_q + (lane & 1) * 2048 + cta * 16 + (lane >> 1), (lane & 1) ? pack2(o1, s2.y) : pack2(s2.x, o0), tag, true);
        }
        mbar_arrive_if(bars + 8 * B_WQFREE, 1, tid == 256);
        poll2<4, false>(mod + 3 * DM + col0, moff, v, tag, true);
#pragma unroll
        for (int i = 0; i < 4; i++) { sbv[i] = bf_sel(v[i], fb); cbv[i] = rbf(1.f + bf_sel(v[4 + i], fb)); }
        if (warp < 2) {
            uint32_t qv[2];
            poll2<1, true>(gs->ex_q + bat * 2048 + kvh * 128 + tid * 2, zoff, qv, tag, true);
            sts64_if(base + OFF_Q + tid * 8, qv[0], qv[1], true);
        }
        bar_comp();
        const int goff[2] = {0, 3 * DM};
        uint32_t gv[4];
        poll2<2, false>(mod + 2 * DM + (rcol & ~1), goff, gv, tag, reducer && warp == RED_WARP);
        gar = bf_sel((lane & 1) ? gv[1] : gv[0], rb_);
        gbr = bf_sel((lane & 1) ? gv[3] : gv[2], rb_);
    }

    const int line0 = rr * 9 + warp;
    const uint32_t rowa = base + line0 * 128;
    const uint32_t lsw = line0 & 7;
    uint32_t wf[4][4][4];
    const uint32_t tg0 = 1 + tag % 3, tg1 = 1 + (2 * (tag % 3)) % 3, tg2 = 1 + (2 * (tag % 3) + 1) % 3;
    unsigned long long* x1dst = gs->ex_x1 + ((lane >> 3) & 1) * 288 + cta * 8 + rb_ * 4 + ((lane >> 1) & 3);
    uint32_t* part = gs->ex_part + cta * (DM * 2) + (warp * 4 + t) * 32 + g * 4;
    const bool x1pub = reducer && warp == RED_WARP && (lane & 1) == 0;
    auto prewrite = [&]() { st_t4(part, 0u, 0u, 0u, 0u); st_w1(x1dst, 0u, 0u, x1pub); };
    auto publish = [&](const float (&acc)[4][4], uint32_t tg) {
        st_t4(part, tagf(sel4(t, acc[0][0], acc[1][0], acc[2][0], acc[3][0]), tg), tagf(sel4(t, acc[0][1], acc[1][1], acc[2][1], acc[3][1]), tg),
              tagf(sel4(t, acc[0][2], acc[1][2], acc[2][2], acc[3][2]), tg), tagf(sel4(t, acc[0][3], acc[1][3], acc[2][3], acc[3][3]), tg));
    };

    if (warp < 8) {
        uint4 qf[4];
#pragma unroll
        for (int j = 0; j < 4; j++) qf[j] = lds128(base + OFF_Q + (g & 1) * 256 + ((j ^ ((g >> 1) & 1)) << 6) + t * 16);
        float mx0 = -INFINITY, mx1 = -INFINITY;
        const uint32_t rowoff = base + ((warp & 1) * 16 + g) * 256 + t * 16;
        const uint32_t sw = (g & 1) << 6;
        const bool valid = (g & 1) == (t & 1);
        uint32_t scp = s_sc + (warp * 16 + g + ((t & 2) << 2)) * 4;
#pragma unroll 1
        for (int c = warp >> 1; c < 32; c += 4) {
            const int s = c + S0 >= NS ? c + S0 - NS : c + S0;
            mbar_wait(bars + 8 * (U_KV + c));
            const uint32_t a0 = rowoff + s * CH;
            float acc[4] = {}, acc2[4] = {};
#pragma unroll
            for (int j = 0; j < 4; j++) {
                const uint32_t o = (j << 6) ^ sw;
                const uint4 lo = lds128(a0 + o), hi = lds128(a0 + 2048 + o);
                mma(acc, lo.x, hi.x, lo.y, hi.y, qf[j].x, qf[j].y);
                mma(acc2, lo.z, hi.z, lo.w, hi.w, qf[j].z, qf[j].w);
            }
            __syncwarp();
            mbar_arrive_if(bars + 8 * (B_USED + c), 4, lane == 0);
            float u0 = (t & 2) ? acc[2] + acc2[2] : acc[0] + acc2[0];
            float u1 = (t & 2) ? acc[3] + acc2[3] : acc[1] + acc2[1];
            u0 = rbf(rbf(u0) * 0.08838834764831845f);
            u1 = rbf(rbf(u1) * 0.08838834764831845f);
            sts32_if(scp, fu(u0), valid);
            sts32_if(scp + 4096, fu(u1), valid);
            mx0 = valid ? fmaxf(mx0, u0) : mx0;
            mx1 = valid ? fmaxf(mx1, u1) : mx1;
            scp += 512;
        }
#pragma unroll
        for (int m = 1; m < 32; m <<= 1) {
            mx0 = fmaxf(mx0, __shfl_xor_sync(0xffffffffu, mx0, m));
            mx1 = fmaxf(mx1, __shfl_xor_sync(0xffffffffu, mx1, m));
        }
        sts64_if(s_stats + warp * 8, fu(mx0), fu(mx1), lane == 0);
        bar_256();
        const int uh = g & 1;
        float mloc = -INFINITY;
#pragma unroll
        for (int w = 0; w < 8; w++) mloc = fmaxf(mloc, lds_f(s_stats + (2 * w + uh) * 4));
        float e[8];
#pragma unroll
        for (int i = 0; i < 4; i++) {
            const float2 v = lds_f2(s_sc + (uh * 1024 + (tid >> 3) * 32 + 2 * t + i * 8) * 4);
            e[2 * i] = __expf(v.x - mloc);
            e[2 * i + 1] = __expf(v.y - mloc);
        }
        float l = ((e[0] + e[1]) + (e[2] + e[3])) + ((e[4] + e[5]) + (e[6] + e[7]));
        l += __shfl_xor_sync(0xffffffffu, l, 1);
        l += __shfl_xor_sync(0xffffffffu, l, 2);
        l += __shfl_xor_sync(0xffffffffu, l, 8);
        l += __shfl_xor_sync(0xffffffffu, l, 16);
        sts32_if(s_stats + (16 + 2 * warp + uh) * 4, fu(l), (lane & ~4) == 0);
        bar_256();
        if (warp == 0) {
            float lt = 0.f;
#pragma unroll
            for (int w = 0; w < 8; w++) lt += lds_f(s_stats + (16 + 2 * w + uh) * 4);
            st_w2(gs->ex_ml + cta * 4 + uh * 2, fu(mloc), fu(lt), tag, (lane & ~4) == 0);
            uint32_t ml[2];
            poll2<1, true>(gs->ex_ml + ((cta & ~3) + t) * 4 + uh * 2, zoff, ml, tag, true);
            const float ms = uf(ml[0]), ls = uf(ml[1]);
            float M = fmaxf(ms, __shfl_xor_sync(0xffffffffu, ms, 1));
            M = fmaxf(M, __shfl_xor_sync(0xffffffffu, M, 2));
            float L = ls * __expf(ms - M);
            L += __shfl_xor_sync(0xffffffffu, L, 1);
            L += __shfl_xor_sync(0xffffffffu, L, 2);
            sts32_if(s_stats + (32 + uh) * 4, fu(__expf(mloc - M) / L), (lane & ~4) == 0);
        }
        bar_256();
        const float f = lds_f(s_stats + (32 + uh) * 4);
        sts128_if(base + OFF_P + tid * 16, pack2(e[0] * f, e[1] * f), pack2(e[2] * f, e[3] * f), pack2(e[4] * f, e[5] * f),
                  pack2(e[6] * f, e[7] * f), true);
        bar_256();

        float acc[4] = {}, acc2[4] = {};
        const int cc = (warp & 3) * 2 + hi8;
        const uint32_t voff = base + (warp >> 2) * (CH / 2) + rr * 128 + ((cc ^ (lane & 7)) << 4);
        uint32_t poff = base + OFF_P + (g & 1) * 64 + t * 16;
        uint32_t* odst = gs->ex_o + cta * 256 + (t & 1) * 128 + warp * 16 + ((t & 2) << 2) + g;
#pragma unroll 1
        for (int c = 32; c < 64; c++) {
            const int s = c + S0 >= 2 * NS ? c + S0 - 2 * NS : c + S0 - NS;
            if (c == PREWRITE_AT) { st_t1(odst, 0u); prewrite(); }
            const uint4 p0 = lds128(poff);
            poff += 128;
            mbar_wait(bars + 8 * (U_KV + c));
            uint32_t a[4], a2[4];
            ldsm4t(a, voff + s * CH);
            ldsm4t(a2, voff + s * CH + 2048);
            mma(acc, a, p0.x, p0.y);
            mma(acc2, a2, p0.z, p0.w);
            __syncwarp();
            mbar_arrive_if(bars + 8 * (B_USED + c), 1, lane == 0);
        }
        st_t1(odst, tagf(sel4(t, acc[0] + acc2[0], acc[1] + acc2[1], acc[2] + acc2[2], acc[3] + acc2[3]), tg0));
    } else {
        mbar_wait(bars + 8 * (U_KV + PREWRITE_AT));
        prewrite();
    }
    {
#pragma unroll
        for (int ks = 0; ks < 2; ks++) {
            mbar_wait(bars + 8 * (U_WO + 2 * ks)); mbar_wait(bars + 8 * (U_WO + 2 * ks + 1));
#pragma unroll
            for (int mt = 0; mt < 4; mt++) ldsm4t(wf[ks][mt], rowa + OFF_WO + ks * 18432 + (((mt * 2 + hi8) ^ lsw) << 4));
        }
        asm volatile("bar.sync 4, 320;" ::: "memory");
        const uint4 ob = lds128(base + OFF_OB + fb * 64 + t * 16);
        float acc[4][4] = {};
#pragma unroll
        for (int mt = 0; mt < 4; mt++) mma(acc[mt], wf[0][mt], ob.x, ob.y);
#pragma unroll
        for (int mt = 0; mt < 4; mt++) mma(acc[mt], wf[1][mt], ob.z, ob.w);
        publish(acc, tg1);
        announce(cnt[C_AO][lane & (RCNT - 1)], warp == 8 && lane < RCNT0);
    }
    const uint32_t gub = bars + 8 * (U_GU + 2 * (warp / 3));
    const uint32_t gxb = heavy ? bars + 8 * (U_GX + 2 * (warp / 3)) : gub;
    uint32_t dn[3][4][4];
    auto load_gu = [&]() {
        const uint32_t rb = base + OFF_GU + hi8 * 36864 + (warp * 64 + rr) * 64;
#pragma unroll
        for (int ks = 0; ks < 4; ks++)
#pragma unroll
            for (int j = 0; j < 4; j++) ldsm4t(wf[ks][j], rb + ks * 1024 + ((j ^ ((rr >> 1) & 3)) << 4));
        if (heavy) {
            const uint32_t rx = base + OFF_GX + hi8 * 18432 + (warp * 64 + rr) * 32;
#pragma unroll
            for (int ks = 0; ks < 4; ks++)
#pragma unroll
                for (int j = 0; j < 2; j++) ldsm4t(dn[1 + j][ks], rx + ks * 512 + ((j ^ ((rr >> 2) & 1)) << 4));
        }
    };
    auto load_dn = [&](int ks) {
#pragma unroll
        for (int mt = 0; mt < 4; mt++) ldsm4t(dn[ks][mt], rowa + OFF_DN + ks * 18432 + (((mt * 2 + hi8) ^ lsw) << 4));
    };
    auto dn_in = [&](int ks) {
        return __all_sync(0xffffffffu, mbar_test(bars + 8 * (U_DN + 2 * ks)) && mbar_test(bars + 8 * (U_DN + 2 * ks + 1)));
    };
    bool have_gu = false, have_dn = false;
    auto try_gu = [&]() {
        if (!have_gu && __all_sync(0xffffffffu, mbar_test(gxb + 8) && mbar_test(gxb) && mbar_test(gub + 8) && mbar_test(gub))) {
            load_gu();
            have_gu = true;
        }
    };
    auto gate = [&](uint32_t gb) {
        unsigned n = 0;
        while (true) {
            try_gu();
            if (__all_sync(0xffffffffu, have_gu ? mbar_try(gb) : mbar_test(gb))) break;
            if (++n > 64 * SPIN_LIMIT) __trap();
        }
    };
    const uint32_t* rsrc = gs->ex_part + (warp & 7) * 16 * (DM * 2) + cta * 32 + lane;
    float x1r = 0.f;
    if (reducer) {
        gate(bars + 8 * B_GATE_AO);
        if (warp < 8) reduce_part1(rsrc, s_r2, warp, lane, tg1);
        bar_comp();
        if (warp == RED_WARP) {
            x1r = rbf(xr + rbf(gar * rbf(reduce_part2(s_r2, lane))));
            const float other = __shfl_xor_sync(0xffffffffu, x1r, 1);
            st_w1(x1dst, pack2(x1r, other), tag, x1pub);
            announce(cnt[C_X1][lane & (RCNT - 1)], lane < RCNT);
        }
    }
    gate(bars + 8 * B_GATE_X1);
    {
        unsigned long long w0, w1;
        unsigned n = 0;
        while (true) {
            asm volatile("ld.relaxed.gpu.global.b64 %0, [%1];" : "=l"(w0) : "l"(gs->ex_x1 + tid) : "memory");
            asm volatile("ld.relaxed.gpu.global.b64 %0, [%1];" : "=l"(w1) : "l"(gs->ex_x1 + 288 + tid) : "memory");
            try_gu();
            if (!have_dn && dn_in(0)) { load_dn(0); have_dn = true; }
            if (__all_sync(0xffffffffu, (uint32_t)(w0 >> 32) == tag && (uint32_t)(w1 >> 32) == tag)) break;
            if (++n > SPIN_LIMIT) __trap();
        }
        y[0] = bf_lo((uint32_t)w0); y[1] = bf_hi((uint32_t)w0); y[2] = bf_lo((uint32_t)w1); y[3] = bf_hi((uint32_t)w1);
        ln_part1(y, s_stats, warp, lane);
        if (!have_gu) { mbar_wait(gub); mbar_wait(gub + 8); mbar_wait(gxb); mbar_wait(gxb + 8); load_gu(); }
        bar_comp();
        ln_part2(y, s_stats, lane);
        uint32_t bfr[4][2];
        spread_b(bfr, pack2(rbf(y[0] * cbv[0]) + sbv[0], rbf(y[1] * cbv[1]) + sbv[1]),
                 pack2(rbf(y[2] * cbv[2]) + sbv[2], rbf(y[3] * cbv[3]) + sbv[3]), lane);
        const uint32_t red = s_sc + (warp * 48 + g + t * 8) * 16;
        float acc[4][4] = {};
#pragma unroll
        for (int ks = 0; ks < 4; ks++)
#pragma unroll
            for (int j = 0; j < 4; j++) mma(acc[j], wf[ks][j], bfr[ks][0], bfr[ks][1]);
        if (heavy) {
            float ax[2][4] = {};
#pragma unroll
            for (int ks = 0; ks < 4; ks++)
#pragma unroll
                for (int j = 0; j < 2; j++) mma(ax[j], dn[1 + j][ks], bfr[ks][0], bfr[ks][1]);
            sts128_if(red + 512, fu(t ? ax[1][0] : ax[0][0]), fu(t ? ax[1][1] : ax[0][1]), fu(t ? ax[1][2] : ax[0][2]),
                      fu(t ? ax[1][3] : ax[0][3]), t < 2);
        }
        sts128_if(red, fu(sel4(t, acc[0][0], acc[1][0], acc[2][0], acc[3][0])), fu(sel4(t, acc[0][1], acc[1][1], acc[2][1], acc[3][1])),
                  fu(sel4(t, acc[0][2], acc[1][2], acc[2][2], acc[3][2])), fu(sel4(t, acc[0][3], acc[1][3], acc[2][3], acc[3][3])), true);
        asm volatile("bar.arrive 6, 320;" ::: "memory");
    }
    {
        bool got[3];
#pragma unroll
        for (int ks = 0; ks < 3; ks++) {
            got[ks] = ks == 0 && have_dn;
            if (!got[ks] && (ks < 2 || heavy) && dn_in(ks)) { load_dn(ks); got[ks] = true; }
        }
        asm volatile("bar.sync 7, 320;" ::: "memory");
        uint32_t hb[6];
#pragma unroll
        for (int i = 0; i < 6; i++) hb[i] = fu(lds_f(base + OFF_HH + (fb * 32 + t + i * 4) * 4));
        float acc[4][4] = {};
#pragma unroll
        for (int ks = 0; ks < 3; ks++) {
            if (ks < 2 || heavy) {
                if (!got[ks]) {
                    mbar_wait(bars + 8 * (U_DN + 2 * ks)); mbar_wait(bars + 8 * (U_DN + 2 * ks + 1));
                    load_dn(ks);
                }
#pragma unroll
                for (int mt = 0; mt < 4; mt++) mma(acc[mt], dn[ks][mt], hb[2 * ks], hb[2 * ks + 1]);
            }
        }
        publish(acc, tg2);
    }
    if (reducer) {
        if (warp < 8) reduce_part1(rsrc, s_r2, warp, lane, tg2);
        bar_comp();
        if (warp == RED_WARP) {
            const float r = x1r + rbf(gbr * rbf(reduce_part2(s_r2, lane)));
            const float other = __shfl_xor_sync(0xffffffffu, r, 1);
            if (x1pub) *reinterpret_cast<uint32_t*>(out + rb_ * DM + rcol) = pack2(r, other);
            if (cta == 0 && lane == 0) st_t1(&gs->epoch, tag);
        }
    }
}

typedef CUresult (*EncodeFn)(CUtensorMap*, CUtensorMapDataType, cuuint32_t, void*, const cuuint64_t*, const cuuint64_t*,
                             const cuuint32_t*, const cuuint32_t*, CUtensorMapInterleave, CUtensorMapSwizzle,
                             CUtensorMapL2promotion, CUtensorMapFloatOOBfill);

void make_map(EncodeFn enc, CUtensorMap* m, const void* p, uint64_t cols, uint64_t rows, uint32_t bc, uint32_t br,
              CUtensorMapSwizzle sw, CUtensorMapL2promotion prom, bool split_halves = false) {
    cuuint64_t gd[3] = {split_halves ? cols / 2 : cols, rows, split_halves ? 2u : 1u};
    cuuint64_t gs[2] = {cols * 2, split_halves ? cols : cols * 2 * rows};
    cuuint32_t bx[3] = {bc, br, split_halves ? 2u : 1u};
    cuuint32_t es[3] = {1, 1, 1};
    enc(m, CU_TENSOR_MAP_DATA_TYPE_BFLOAT16, 3, const_cast<void*>(p), gd, gs, bx, es, CU_TENSOR_MAP_INTERLEAVE_NONE, sw, prom,
        CU_TENSOR_MAP_FLOAT_OOB_FILL_NONE);
}

void build_ops(uint4* list, bool heavy) {
    constexpr int NMAX = NOPS_HEAVY + NPRE;
    uint4 op[NMAX];
    int order[NMAX], n = 0;
    for (int u = 0; u < 3; u++) order[n++] = heavy ? U_WQ + u : u;
    for (int u = U_KV; u < U_KV + K_AT_START; u++) order[n++] = u;
    if (!heavy) for (int u = 0; u < 3; u++) order[n++] = U_WQ + u;
    for (int u = U_KV + K_AT_START; u < U_WO; u++) order[n++] = u;
    const int n_v = n;
    for (int k = 0; k < 4; k++) order[n++] = U_WO + k;
    for (int k = 0; k < 3; k++) {
        order[n++] = U_GU + 2 * k; order[n++] = U_GU + 2 * k + 1;
        if (heavy) { order[n++] = U_GX + 2 * k; order[n++] = U_GX + 2 * k + 1; }
    }
    for (int k = 0; k < (heavy ? 6 : 4); k++) order[n++] = U_DN + k;
    int kb[NMAX], win[NMAX], cum[NMAX + 1];
    cum[0] = 0;
    for (int i = 0; i < n; i++) {
        const int u = order[i];
        int dst, sel0 = 0, sel1 = 0, row = 0, map, spb = -1;
        win[i] = WIN_TAIL;
        if (u < U_KV || (u >= U_WQ && u < U_GX)) {
            const int k = u < U_KV ? u : u - U_WQ + 3;
            map = k < 3 ? M_WMOD : M_WQ; dst = OFF_WMOD + k * 12288; sel0 = 1; row = (k % 3) * 192; kb[i] = 12;
            spb = B_DONE; win[i] = WIN_MID;
        } else if (u < U_WO) {
            const int c = u - U_KV, slot = (c + S0) % NS;
            map = c < 32 ? M_K : M_V; dst = slot * CH; sel1 = 1; row = ((c & 31) >> 1) * 256 + (c & 1) * 32; kb[i] = 8;
            spb = c >= NS ? B_USED + c - NS : (slot >= 9 && slot <= 13) ? B_WQFREE : (slot >= 5 && slot < 9) ? B_MODFREE : B_DONE;
            win[i] = c < 64 - END_CHUNKS ? WIN_MID : WIN_END;
        } else if (u < U_GU) {
            const int k = u - U_WO;
            map = M_WO; dst = OFF_WO + k * 9216; sel1 = 4; row = k * 72; kb[i] = 9; win[i] = WIN_END;
        } else if (u < U_WQ) {
            const int k = u - U_GU;
            map = M_GATE + (k & 1); dst = OFF_GU + (k & 1) * 36864 + (k >> 1) * 12288; sel0 = 1; row = (k >> 1) * 192; kb[i] = 12;
        } else if (u < U_DN) {
            const int k = u - U_GX;
            map = M_GATEX + (k & 1); dst = OFF_GX + (k & 1) * 18432 + (k >> 1) * 6144; sel0 = 2; row = (k >> 1) * 192; kb[i] = 6;
        } else {
            const int k = u - U_DN;
            map = M_DN; dst = OFF_DN + k * 9216; kb[i] = 9; win[i] = WIN_LAST;
            if (k < 4) { sel1 = 4; row = k * 72; } else { sel1 = 5; row = (k - 4) * 72; }
        }
        if (heavy && i >= n_v) win[i] += WIN_HEAVY_EXTRA;
        if (spb < 0) spb = B_USED + 64 - NS + ((dst + kb[i] * 1024 - 1) >> 13);
        cum[i + 1] = cum[i] + kb[i];
        op[i].x = (dst >> 8) | (sel0 << 10) | (sel1 << 12) | (map << 15) | (kb[i] << 19) | ((unsigned)u << 24) |
                  ((i == n_v - ANCHOR_BACK || i == n_v - ANCHOR_BACK + 1) ? 1u << 23 : 0u);
        op[i].y = row | (spb << 12);
    }
    const double tv = heavy ? PACE_TV_HEAVY : PACE_TV;
    for (int i = 0; i < n; i++) {
        double due = i <= n_v ? PACE_T0 + (tv - PACE_T0) * cum[i] / cum[n_v] : tv + (PACE_TE - tv) * (cum[i] - cum[n_v]) / (cum[n] - cum[n_v]);
        if (due < 0) due = 0;
        op[i].y |= (unsigned)(due / 16) << 20;
        unsigned long long lv = 0;
        for (int l = 0; l < 8; l++) {
            int w = win[i] + (l - PACE_MID) * PACE_STEP, wd = B_DONE;
            if (w < PACE_WMIN) w = PACE_WMIN;
            if (w > PACE_WMAX) w = PACE_WMAX;
            if (i >= n_v && w > win[i] + TAIL_UP) w = win[i] + TAIL_UP;
            for (int j = i - 1; j >= 0; j--)
                if (cum[i + 1] - cum[j] > w) { wd = order[j]; break; }
            lv |= (unsigned long long)wd << (8 * l);
        }
        op[i].z = (unsigned)lv;
        op[i].w = (unsigned)(lv >> 32);
        if (i >= NPRE) list[i - NPRE] = op[i];
    }
}

}

extern "C" void kernel_launch(void* const* d_in, const int* in_sizes, int n_in, void* d_out, int out_size) {
    (void)in_sizes; (void)n_in; (void)out_size;
    const __nv_bfloat16* x = (const __nv_bfloat16*)d_in[0];
    const __nv_bfloat16* kc = (const __nv_bfloat16*)d_in[1];
    const __nv_bfloat16* vc = (const __nv_bfloat16*)d_in[2];
    const __nv_bfloat16* wq = (const __nv_bfloat16*)d_in[3];
    const __nv_bfloat16* wo = (const __nv_bfloat16*)d_in[4];
    const __nv_bfloat16* wg = (const __nv_bfloat16*)d_in[6];
    const __nv_bfloat16* wu = (const __nv_bfloat16*)d_in[7];
    const __nv_bfloat16* wd = (const __nv_bfloat16*)d_in[8];
    const __nv_bfloat16* cv = (const __nv_bfloat16*)d_in[9];
    const __nv_bfloat16* wm = (const __nv_bfloat16*)d_in[10];

    EncodeFn enc = nullptr;
    cudaDriverEntryPointQueryResult qr;
    cudaGetDriverEntryPoint("cuTensorMapEncodeTiled", (void**)&enc, cudaEnableDefault, &qr);
    cudaFuncSetAttribute(fused_block_kernel, cudaFuncAttributeMaxDynamicSharedMemorySize, SMEM_BYTES);
    Params mp;
    const CUtensorMapL2promotion P128 = CU_TENSOR_MAP_L2_PROMOTION_L2_128B, P256 = CU_TENSOR_MAP_L2_PROMOTION_L2_256B;
    make_map(enc, &mp.m[M_WMOD], wm, 6 * DM, DM, 32, 192, CU_TENSOR_MAP_SWIZZLE_64B, P128);
    make_map(enc, &mp.m[M_WQ], wq, 4096, DM, 32, 192, CU_TENSOR_MAP_SWIZZLE_64B, P128);
    make_map(enc, &mp.m[M_K], kc, 128, (uint64_t)2 * 16 * SK, 128, 32, CU_TENSOR_MAP_SWIZZLE_NONE, P256);
    make_map(enc, &mp.m[M_V], vc, 128, (uint64_t)2 * 16 * SK, 64, 32, CU_TENSOR_MAP_SWIZZLE_128B, P256, true);
    make_map(enc, &mp.m[M_WO], wo, 64, 4096 * 9, 64, 72, CU_TENSOR_MAP_SWIZZLE_128B, P256);
    make_map(enc, &mp.m[M_DN], wd, 64, FF * 9, 64, 72, CU_TENSOR_MAP_SWIZZLE_128B, P256);
    make_map(enc, &mp.m[M_GATE], wg, FF, DM, 32, 192, CU_TENSOR_MAP_SWIZZLE_64B, P128);
    make_map(enc, &mp.m[M_UP], wu, FF, DM, 32, 192, CU_TENSOR_MAP_SWIZZLE_64B, P128);
    make_map(enc, &mp.m[M_GATEX], wg, FF, DM, 16, 192, CU_TENSOR_MAP_SWIZZLE_32B, P128);
    make_map(enc, &mp.m[M_UPX], wu, FF, DM, 16, 192, CU_TENSOR_MAP_SWIZZLE_32B, P128);
    build_ops(mp.op, false);
    build_ops(mp.op + NOPS_LIGHT, true);
    for (int i = 3; i < 9; i++) {
        const int blk = i / 3, bar = (blk == 1 ? U_WQ : 3) + i % 3;
        mp.op[NOPS_LIGHT + NOPS_HEAVY + i - 3] =
            make_uint4(((OFF_WMOD + i * 12288) >> 8) | ((blk + 1) << 10) | (M_WMOD << 15) | (12 << 19) | (bar << 24),
                       (i % 3) * 192 | (B_DONE << 12), B_DONE * 0x01010101u, B_DONE * 0x01010101u);
    }
    Scratch* gs = nullptr;
    cudaGetSymbolAddress((void**)&gs, g_scratch);
    fused_block_kernel<<<NCTA + NHELP, NTHR, SMEM_BYTES>>>(x, cv, (__nv_bfloat16*)d_out, gs, (const char*)kc, mp);
}
```

```cpp
#include <cuda_runtime.h>
#include <cuda.h>
#include <cuda_bf16.h>
#include <stdint.h>

namespace {

constexpr int DM = 576;
constexpr int FF = 4608;
constexpr int SK = 32768;
constexpr int WIN = 4096;
constexpr int NCTA = 128;
constexpr int NHELP = 4;
constexpr int NTHR = 384;
constexpr int NRED = 36;
constexpr int RED_WARP = 8;

constexpr int WIN_MID = 40, WIN_END = 48, WIN_TAIL = 32, WIN_LAST = 36;
constexpr int WIN_HEAVY_EXTRA = 12, END_CHUNKS = 8;
constexpr int PACE_T0 = -500, PACE_TV = 22700, PACE_TV_HEAVY = 22500, PACE_TE = 29200;
constexpr int PACE_MID = 3, PACE_STEP = 8, PACE_SHIFT = 8;
constexpr int PACE_WMIN = 18, PACE_WMAX = 64, TAIL_UP = 8;
constexpr int ANCHOR_BACK = 8, ANCHOR_BIAS = 650;
constexpr int NMS = 4, MS_FIRST = 10, MS_STEP = 13, MS_DELAY = 5, MS_BIAS = 0, MS_RANK = 47, ANCHOR_NUM = 4;
constexpr int K_AT_START = 2;
constexpr int REP1 = 8;
constexpr int RCNT = 8, RCNT0 = 4;
constexpr unsigned HINT_MOD = 36, HINT_AO = 112, HINT_X1 = 28;
constexpr int PREWRITE_AT = 54;
constexpr int SLEEP_NS = 100;
constexpr unsigned SPIN_LIMIT = 1u << 22;

constexpr int CH = 8192;
constexpr int NS = 26;
constexpr int S0 = 14;
constexpr int OFF_WMOD = 40960;
constexpr int OFF_WQ = 77824;
constexpr int OFF_WO = 0;
constexpr int OFF_GU = 36864;
constexpr int OFF_GX = 110592;
constexpr int OFF_DN = 147456;
constexpr int OFF_SC = NS * CH;
constexpr int OFF_P = OFF_SC + 8192;
constexpr int OFF_Q = OFF_P + 4096;
constexpr int OFF_ST = OFF_Q + 512;
constexpr int OFF_HH = OFF_ST + 256;
constexpr int OFF_R2 = OFF_HH + 256;
constexpr int OFF_OB = OFF_R2 + 1024;
constexpr int OFF_T0 = OFF_OB + 128;
constexpr int OFF_BAR = OFF_T0 + 128;
constexpr int SMEM_BYTES = OFF_BAR + 192 * 8 + 1024;
static_assert(SMEM_BYTES <= 232448, "smem");

constexpr int U_KV = 3;
constexpr int U_WO = 67;
constexpr int U_GU = 71;
constexpr int U_WQ = 80;
constexpr int U_GX = 83;
constexpr int U_DN = 89;
constexpr int B_DONE = 95;
constexpr int B_MODFREE = 96, B_WQFREE = 97;
constexpr int B_GATE_AO = 98, B_GATE_X1 = 99, B_GATE_MOD = 100;
constexpr int B_USED = 128;

enum { M_WMOD, M_WQ, M_K, M_V, M_WO, M_DN, M_GATE, M_UP, M_GATEX, M_UPX, M_COUNT };
constexpr int NPRE = 3 + K_AT_START;
constexpr int NOPS_LIGHT = 84 - NPRE, NOPS_HEAVY = 89 - NPRE, NOPS_HELP = 6;
struct Params { CUtensorMap m[M_COUNT]; uint4 op[NOPS_LIGHT + NOPS_HEAVY + NOPS_HELP]; int nom[4]; };

enum { C_AO, C_X1, C_PACE, C_MOD, C_COUNT };
static_assert(sizeof(Params) + 64 <= 4096, "kernel parameters");
struct __align__(128) Scratch {
    unsigned int epoch;
    unsigned int pad[31];
    unsigned int cnt[3][C_COUNT][RCNT][32];
    unsigned long long ex_mod[REP1 * 6 * DM];
    unsigned long long ex_q[2 * 2048];
    unsigned long long ex_x1[DM];
    unsigned long long ex_ml[NCTA * 4];
    unsigned long long ex_pace[4 * RCNT * 16];
    uint32_t ex_o[NCTA * 256];
    uint32_t ex_part[NCTA * DM * 2];
};
__device__ Scratch g_scratch;

__device__ __forceinline__ uint32_t fu(float x) { return __float_as_uint(x); }
__device__ __forceinline__ float uf(uint32_t x) { return __uint_as_float(x); }
__device__ __forceinline__ uint32_t now_ns() { uint32_t t; asm volatile("mov.u32 %0, %globaltimer_lo;" : "=r"(t)); return t; }
__device__ __forceinline__ void mbar_init(uint32_t b, int c) {
    asm volatile("mbarrier.init.shared::cta.b64 [%0], %1;" ::"r"(b), "r"(c) : "memory");
}
__device__ __forceinline__ void mbar_init_fence() { asm volatile("fence.mbarrier_init.release.cluster;" ::: "memory"); }
__device__ __forceinline__ void mbar_expect(uint32_t b, uint32_t bytes) {
    asm volatile("mbarrier.arrive.expect_tx.shared::cta.b64 _, [%0], %1;" ::"r"(b), "r"(bytes) : "memory");
}
__device__ __forceinline__ void mbar_arrive_if(uint32_t b, uint32_t cnt, bool p) {
    asm volatile("{\n.reg .pred p;\nsetp.ne.u32 p, %2, 0;\n@p mbarrier.arrive.shared::cta.b64 _, [%0], %1;\n}"
                 ::"r"(b), "r"(cnt), "r"((uint32_t)p) : "memory");
}
__device__ __forceinline__ bool mbar_try(uint32_t b) {
    uint32_t ok;
    asm volatile("{\n.reg .pred p;\nmbarrier.try_wait.parity.shared::cta.b64 p, [%1], 0;\nselp.u32 %0, 1, 0, p;\n}"
                 : "=r"(ok) : "r"(b) : "memory");
    return ok;
}
__device__ __forceinline__ bool mbar_test(uint32_t b) {
    uint32_t ok;
    asm volatile("{\n.reg .pred p;\nmbarrier.test_wait.parity.shared::cta.b64 p, [%1], 0;\nselp.u32 %0, 1, 0, p;\n}"
                 : "=r"(ok) : "r"(b) : "memory");
    return ok;
}
__device__ __forceinline__ void mbar_wait(uint32_t b) {
    unsigned n = 0;
    while (!mbar_try(b))
        if (++n > SPIN_LIMIT) __trap();
}
__device__ __forceinline__ void tma3d(uint32_t dst, const CUtensorMap* m, int c0, int c1, uint32_t bar) {
    asm volatile("cp.async.bulk.tensor.3d.shared::cluster.global.mbarrier::complete_tx::bytes [%0], [%1, {%3, %4, %5}], [%2];"
                 ::"r"(dst), "l"(m), "r"(bar), "r"(c0), "r"(c1), "r"(0) : "memory");
}
__device__ __forceinline__ void tma3d_hint(uint32_t dst, const CUtensorMap* m, int c0, int c1, uint32_t bar, uint64_t pol) {
    asm volatile("cp.async.bulk.tensor.3d.shared::cluster.global.mbarrier::complete_tx::bytes.L2::cache_hint [%0], [%1, {%3, %4, %5}], [%2], %6;"
                 ::"r"(dst), "l"(m), "r"(bar), "r"(c0), "r"(c1), "r"(0), "l"(pol) : "memory");
}
__device__ __forceinline__ bool elect_one() {
    uint32_t p;
    asm volatile("{\n.reg .pred p;\nelect.sync _|p, 0xffffffff;\nselp.u32 %0, 1, 0, p;\n}" : "=r"(p));
    return p;
}
__device__ __forceinline__ uint32_t ldg32(const void* p) {
    uint32_t v;
    asm volatile("ld.global.nc.u32 %0, [%1];" : "=r"(v) : "l"(p));
    return v;
}
__device__ __forceinline__ void bar_comp() { asm volatile("bar.sync 1, 288;" ::: "memory"); }
__device__ __forceinline__ void bar_256() { asm volatile("bar.sync 2, 256;" ::: "memory"); }
__device__ __forceinline__ void sts16(uint32_t a, uint32_t v) { asm volatile("st.shared.b16 [%0], %1;" ::"r"(a), "h"((unsigned short)v) : "memory"); }
__device__ __forceinline__ void sts32_if(uint32_t a, uint32_t v, bool p) {
    asm volatile("{\n.reg .pred p;\nsetp.ne.u32 p, %2, 0;\n@p st.shared.b32 [%0], %1;\n}" ::"r"(a), "r"(v), "r"((uint32_t)p) : "memory");
}
__device__ __forceinline__ void sts64_if(uint32_t a, uint32_t v0, uint32_t v1, bool p) {
    asm volatile("{\n.reg .pred p;\nsetp.ne.u32 p, %3, 0;\n@p st.shared.v2.b32 [%0], {%1, %2};\n}" ::"r"(a), "r"(v0), "r"(v1), "r"((uint32_t)p) : "memory");
}
__device__ __forceinline__ void sts128_if(uint32_t a, uint32_t v0, uint32_t v1, uint32_t v2, uint32_t v3, bool p) {
    asm volatile("{\n.reg .pred p;\nsetp.ne.u32 p, %5, 0;\n@p st.shared.v4.b32 [%0], {%1, %2, %3, %4};\n}"
                 ::"r"(a), "r"(v0), "r"(v1), "r"(v2), "r"(v3), "r"((uint32_t)p) : "memory");
}
__device__ __forceinline__ float lds_f(uint32_t a) { float v; asm volatile("ld.shared.f32 %0, [%1];" : "=f"(v) : "r"(a) : "memory"); return v; }
__device__ __forceinline__ float2 lds_f2(uint32_t a) {
    float2 v; asm volatile("ld.shared.v2.f32 {%0,%1}, [%2];" : "=f"(v.x), "=f"(v.y) : "r"(a) : "memory"); return v;
}
__device__ __forceinline__ float4 lds_f4(uint32_t a) {
    float4 v; asm volatile("ld.shared.v4.f32 {%0,%1,%2,%3}, [%4];" : "=f"(v.x), "=f"(v.y), "=f"(v.z), "=f"(v.w) : "r"(a) : "memory"); return v;
}
__device__ __forceinline__ uint4 lds128(uint32_t addr) {
    uint4 v;
    asm volatile("ld.shared.v4.u32 {%0,%1,%2,%3}, [%4];" : "=r"(v.x), "=r"(v.y), "=r"(v.z), "=r"(v.w) : "r"(addr) : "memory");
    return v;
}
__device__ __forceinline__ void ldsm4t(uint32_t (&a)[4], uint32_t addr) {
    asm volatile("ldmatrix.sync.aligned.m8n8.x4.trans.shared.b16 {%0,%1,%2,%3}, [%4];"
                 : "=r"(a[0]), "=r"(a[1]), "=r"(a[2]), "=r"(a[3]) : "r"(addr) : "memory");
}
__device__ __forceinline__ void mma(float (&c)[4], uint32_t a0, uint32_t a1, uint32_t a2, uint32_t a3, uint32_t b0, uint32_t b1) {
    asm volatile("mma.sync.aligned.m16n8k16.row.col.f32.bf16.bf16.f32 {%0,%1,%2,%3}, {%4,%5,%6,%7}, {%8,%9}, {%0,%1,%2,%3};"
                 : "+f"(c[0]), "+f"(c[1]), "+f"(c[2]), "+f"(c[3])
                 : "r"(a0), "r"(a1), "r"(a2), "r"(a3), "r"(b0), "r"(b1));
}
__device__ __forceinline__ void mma(float (&c)[4], const uint32_t (&a)[4], uint32_t b0, uint32_t b1) {
    mma(c, a[0], a[1], a[2], a[3], b0, b1);
}

template <bool ATOM>
__device__ __forceinline__ void rd16(unsigned long long& a, unsigned long long& b, const void* p, uint32_t on) {
    if (ATOM)
        asm volatile("{\n.reg .pred p;\n.reg .b128 z, d;\nsetp.ne.u32 p, %3, 0;\nmov.b128 z, {0, 0};\nmov.b128 d, {%0, %1};\n"
                     "@p atom.relaxed.gpu.global.cas.b128 d, [%2], z, z;\nmov.b128 {%0, %1}, d;\n}"
                     : "+l"(a), "+l"(b) : "l"(p), "r"(on) : "memory");
    else
        asm volatile("{\n.reg .pred p;\nsetp.ne.u32 p, %3, 0;\n@p ld.relaxed.gpu.global.v2.b64 {%0, %1}, [%2];\n}"
                     : "+l"(a), "+l"(b) : "l"(p), "r"(on) : "memory");
}
__device__ __forceinline__ void st_w1(unsigned long long* p, uint32_t v, uint32_t tag, bool on) {
    unsigned long long w = ((unsigned long long)tag << 32) | v;
    asm volatile("{\n.reg .pred p;\nsetp.ne.u32 p, %2, 0;\n@p st.relaxed.gpu.global.b64 [%0], %1;\n}" ::"l"(p), "l"(w), "r"((uint32_t)on) : "memory");
}
__device__ __forceinline__ void st_w2(unsigned long long* p, uint32_t v0, uint32_t v1, uint32_t tag, bool on) {
    unsigned long long w0 = ((unsigned long long)tag << 32) | v0, w1 = ((unsigned long long)tag << 32) | v1;
    asm volatile("{\n.reg .pred p;\nsetp.ne.u32 p, %3, 0;\n@p st.relaxed.gpu.global.v2.b64 [%0], {%1, %2};\n}"
                 ::"l"(p), "l"(w0), "l"(w1), "r"((uint32_t)on) : "memory");
}
template <int N, bool ATOM>
__device__ __forceinline__ void poll2(const unsigned long long* p, const int (&off)[N], uint32_t (&v)[2 * N], uint32_t tag, bool on) {
    unsigned long long w[2 * N];
    uint32_t need[N];
#pragma unroll
    for (int i = 0; i < N; i++) { w[2 * i] = w[2 * i + 1] = (unsigned long long)tag << 32; need[i] = on; }
    unsigned n = 0;
    while (true) {
#pragma unroll
        for (int i = 0; i < N; i++) rd16<ATOM>(w[2 * i], w[2 * i + 1], p + off[i], need[i]);
        uint32_t any = 0;
#pragma unroll
        for (int i = 0; i < N; i++) {
            need[i] = ((uint32_t)(w[2 * i] >> 32) ^ tag) | ((uint32_t)(w[2 * i + 1] >> 32) ^ tag);
            any |= need[i];
        }
        if (!__any_sync(0xffffffffu, any != 0)) break;
        __nanosleep(SLEEP_NS);
        if (++n > SPIN_LIMIT) __trap();
    }
#pragma unroll
    for (int i = 0; i < 2 * N; i++) v[i] = (uint32_t)w[i];
}
__device__ __forceinline__ uint32_t tagf(float v, uint32_t tg) { return (fu(v) & ~3u) | tg; }
__device__ __forceinline__ void st_t1(uint32_t* p, uint32_t v) {
    asm volatile("st.relaxed.gpu.global.b32 [%0], %1;" ::"l"(p), "r"(v) : "memory");
}
__device__ __forceinline__ void st_t4(uint32_t* p, uint32_t a, uint32_t b, uint32_t c, uint32_t d) {
    asm volatile("st.relaxed.gpu.global.v4.b32 [%0], {%1, %2, %3, %4};" ::"l"(p), "r"(a), "r"(b), "r"(c), "r"(d) : "memory");
}
template <int N, int STRIDE, bool ATOM>
__device__ __forceinline__ void poll_lines(const uint32_t* p, float (&v)[N], uint32_t tg) {
    uint32_t w[N];
#pragma unroll
    for (int i = 0; i < N; i++) w[i] = 0;
    unsigned n = 0;
    while (true) {
#pragma unroll
        for (int i = 0; i < N; i++) {
            if (ATOM)
                asm volatile("{\n.reg .pred p;\nsetp.ne.u32 p, %2, 0;\n@p atom.relaxed.gpu.global.or.b32 %0, [%1], 0;\n}"
                             : "+r"(w[i]) : "l"(p + i * STRIDE), "r"((w[i] ^ tg) & 3u) : "memory");
            else
                asm volatile("{\n.reg .pred p;\nsetp.ne.u32 p, %2, 0;\n@p ld.relaxed.gpu.global.b32 %0, [%1];\n}"
                             : "+r"(w[i]) : "l"(p + i * STRIDE), "r"((w[i] ^ tg) & 3u) : "memory");
        }
        uint32_t any = 0;
#pragma unroll
        for (int i = 0; i < N; i++) any |= w[i] ^ tg;
        if (!__any_sync(0xffffffffu, (any & 3u) != 0)) break;
        if (++n > SPIN_LIMIT) __trap();
    }
#pragma unroll
    for (int i = 0; i < N; i++) v[i] = uf(w[i] & ~3u);
}
__device__ __forceinline__ void announce(unsigned int* c, bool on) {
    if (on) asm volatile("red.relaxed.gpu.global.add.u32 [%0], 1;" ::"l"(c) : "memory");
}
template <bool SLEEP>
__device__ __forceinline__ void await_count(const unsigned int* p, unsigned target, uint32_t gate, int lane) {
    unsigned n = 0, c;
    while (true) {
        c = 0;
        if (lane == 0) asm volatile("atom.relaxed.gpu.global.or.b32 %0, [%1], 0;" : "=r"(c) : "l"(p) : "memory");
        c = __shfl_sync(0xffffffffu, c, 0);
        if (c >= target) break;
        if (SLEEP) __nanosleep(SLEEP_NS);
        if (++n > SPIN_LIMIT) __trap();
    }
    mbar_arrive_if(gate, 1, lane == 0);
}

__device__ __forceinline__ float rbf(float x) {
    uint32_t r;
    asm("cvt.rn.bf16x2.f32 %0, %1, 0f00000000;" : "=r"(r) : "f"(x));
    return uf(r);
}
__device__ __forceinline__ uint32_t pack2(float lo, float hi) {
    __nv_bfloat162 v = __floats2bfloat162_rn(lo, hi);
    return *reinterpret_cast<uint32_t*>(&v);
}
__device__ __forceinline__ float bf_lo(uint32_t v) { return uf(v << 16); }
__device__ __forceinline__ float bf_hi(uint32_t v) { return uf(v & 0xffff0000u); }
__device__ __forceinline__ float bf_sel(uint32_t v, int hi) { return hi ? bf_hi(v) : bf_lo(v); }
__device__ __forceinline__ float sel4(int t, float a, float b, float c, float d) {
    return (t & 2) ? ((t & 1) ? d : c) : ((t & 1) ? b : a);
}

__device__ __forceinline__ void ln_part1(const float (&v)[4], uint32_t stats, int warp, int lane) {
    float mean = 0.25f * ((v[0] + v[1]) + (v[2] + v[3]));
    float m2;
    { float a = v[0] - mean, b = v[1] - mean, c = v[2] - mean, d = v[3] - mean; m2 = (a * a + b * b) + (c * c + d * d); }
    float cnt_half = 2.f;
#pragma unroll
    for (int s = 0; s < 4; s++) {
        const int mask = (s == 0) ? 1 : (s == 1) ? 2 : (s == 2) ? 8 : 16;
        const float om = __shfl_xor_sync(0xffffffffu, mean, mask);
        const float o2 = __shfl_xor_sync(0xffffffffu, m2, mask);
        const float d = om - mean;
        m2 = (m2 + o2) + d * d * cnt_half;
        mean = 0.5f * (mean + om);
        cnt_half *= 2.f;
    }
    sts64_if(stats + ((lane >> 2) & 1) * 80 + warp * 8, fu(mean), fu(m2), (lane & ~4) == 0);
}
__device__ __forceinline__ void ln_part2(float (&v)[4], uint32_t stats, int lane) {
    const uint32_t st = stats + ((lane >> 2) & 1) * 80;
    const float4 a = lds_f4(st), b = lds_f4(st + 16), c = lds_f4(st + 32), d = lds_f4(st + 48);
    const float2 e = lds_f2(st + 64);
    const float mu = ((((a.x + a.z) + (b.x + b.z)) + ((c.x + c.z) + (d.x + d.z))) + e.x) * (1.f / 9.f);
    const float M2 = (((a.y + a.w) + (b.y + b.w)) + ((c.y + c.w) + (d.y + d.w))) + e.y;
    const float q0 = a.x - mu, q1 = a.z - mu, q2 = b.x - mu, q3 = b.z - mu, q4 = c.x - mu, q5 = c.z - mu, q6 = d.x - mu,
                q7 = d.z - mu, q8 = e.x - mu;
    const float dd = (((q0 * q0 + q1 * q1) + (q2 * q2 + q3 * q3)) + ((q4 * q4 + q5 * q5) + (q6 * q6 + q7 * q7))) + q8 * q8;
    const float mb = rbf(mu);
    const float vb = rbf((M2 + 64.f * dd) * (1.f / 576.f));
    float sq, rd;
    asm("sqrt.approx.f32 %0, %1;" : "=f"(sq) : "f"(rbf(vb + 1e-5f)));
    asm("rcp.approx.f32 %0, %1;" : "=f"(rd) : "f"(rbf(sq)));
#pragma unroll
    for (int i = 0; i < 4; i++) v[i] = rbf(rbf(v[i] - mb) * rd);
}

__device__ __forceinline__ void spread_b(uint32_t (&b)[4][2], uint32_t r0, uint32_t r1, int lane) {
#pragma unroll
    for (int ks = 0; ks < 4; ks++) {
        const int src = (ks << 3) | (lane & 7);
        b[ks][0] = __shfl_sync(0xffffffffu, r0, src);
        b[ks][1] = __shfl_sync(0xffffffffu, r1, src);
    }
}

__device__ __noinline__ void gemv32(uint32_t tile, uint32_t bar, uint32_t r0, uint32_t r1, uint32_t red, int warp) {
    const int lane = threadIdx.x & 31;
    uint32_t b[4][2];
    spread_b(b, r0, r1, lane);
    float acc[2][4] = {};
    const int rr = (lane & 7) + ((lane >> 4) << 3);
    const uint32_t a0 = tile + (warp * 64 + rr) * 64;
    const int sw = (rr >> 1) & 3, c = (lane >> 3) & 1;
    mbar_wait(bar + 8 * (warp / 3));
#pragma unroll
    for (int ks = 0; ks < 4; ks++) {
#pragma unroll
        for (int mt = 0; mt < 2; mt++) {
            uint32_t a[4];
            ldsm4t(a, a0 + ks * 1024 + (((mt * 2 + c) ^ sw) << 4));
            mma(acc[mt], a, b[ks][0], b[ks][1]);
        }
    }
    const int t = lane & 3, g = lane >> 2;
    sts64_if(red + (warp * 32 + t * 8 + g) * 8, fu(sel4(t, acc[0][0], acc[0][2], acc[1][0], acc[1][2])),
             fu(sel4(t, acc[0][1], acc[0][3], acc[1][1], acc[1][3])), true);
}
__device__ __forceinline__ float2 sum9(uint32_t red) {
    float2 v[9];
#pragma unroll
    for (int w = 0; w < 9; w++) v[w] = lds_f2(red + w * 256);
    return make_float2((((v[0].x + v[1].x) + (v[2].x + v[3].x)) + ((v[4].x + v[5].x) + (v[6].x + v[7].x))) + v[8].x,
                       (((v[0].y + v[1].y) + (v[2].y + v[3].y)) + ((v[4].y + v[5].y) + (v[6].y + v[7].y))) + v[8].y);
}

__device__ __forceinline__ void reduce_part1(const uint32_t* p, uint32_t r2, int warp, int lane, uint32_t tg) {
    float v[16];
    poll_lines<16, DM * 2, false>(p, v, tg);
    const float s = (((v[0] + v[1]) + (v[2] + v[3])) + ((v[4] + v[5]) + (v[6] + v[7]))) +
                    (((v[8] + v[9]) + (v[10] + v[11])) + ((v[12] + v[13]) + (v[14] + v[15])));
    sts32_if(r2 + (warp * 32 + (lane >> 2) + (lane & 2) * 4 + (lane & 1) * 16) * 4, fu(s), true);
}
__device__ __forceinline__ float reduce_part2(uint32_t r2, int lane) {
    float a[8];
#pragma unroll
    for (int w = 0; w < 8; w++) a[w] = lds_f(r2 + (w * 32 + lane) * 4);
    return ((a[0] + a[1]) + (a[2] + a[3])) + ((a[4] + a[5]) + (a[6] + a[7]));
}
__device__ __forceinline__ uint32_t next_epoch(const Scratch* gs) {
    uint32_t e;
    asm volatile("ld.relaxed.gpu.global.u32 %0, [%1];" : "=r"(e) : "l"(&gs->epoch) : "memory");
    return e >= 0x7ffffffeu ? 1u : e + 1;
}

__global__ void __launch_bounds__(NTHR, 1)
fused_block_kernel(const __nv_bfloat16* __restrict__ x, const __nv_bfloat16* __restrict__ cvec, __nv_bfloat16* __restrict__ out,
                   Scratch* __restrict__ gs, const char* __restrict__ kbytes, const __grid_constant__ Params mp)
{
    extern __shared__ __align__(1024) unsigned char smem_raw[];
    const uint32_t base = ((uint32_t)__cvta_generic_to_shared(smem_raw) + 1023u) & ~1023u;
    const uint32_t bars = base + OFF_BAR;
    const bool helper = blockIdx.x < NHELP;
    const int cta = helper ? NCTA + blockIdx.x : blockIdx.x - NHELP;
    const bool heavy = cta >= 96;
    const int mblk0 = helper ? 96 + 3 * blockIdx.x : cta;
    const int krow = ((((cta >> 2) & 1) * 16 + (cta >> 3)) * SK + (SK - WIN)) + (cta & 3) * 64;
    if (!helper && threadIdx.x < 128)
        asm volatile("prefetch.global.L2 [%0];" ::"l"(kbytes + (size_t)krow * 256 + (threadIdx.x >> 7) * 65536 + (threadIdx.x & 127) * 128));
    uint32_t t_start = now_ns();

    if (threadIdx.x >= 320) {
        const int lane = threadIdx.x & 31, warp = __shfl_sync(0xffffffffu, threadIdx.x >> 5, 0);
        const int nops = helper ? NOPS_HELP : heavy ? NOPS_HEAVY : NOPS_LIGHT;
        uint4 tab0 = make_uint4(0, 0, 0, 0), tab1 = tab0;
        {
            const uint4* ops = mp.op + (helper ? NOPS_LIGHT + NOPS_HEAVY : heavy ? NOPS_LIGHT : 0);
            const int i0 = (warp & 1) + 2 * lane;
            if (i0 < nops) asm volatile("ld.v4.u32 {%0,%1,%2,%3}, [%4];" : "=r"(tab0.x), "=r"(tab0.y), "=r"(tab0.z), "=r"(tab0.w) : "l"(ops + i0));
            if (i0 + 64 < nops) asm volatile("ld.v4.u32 {%0,%1,%2,%3}, [%4];" : "=r"(tab1.x), "=r"(tab1.y), "=r"(tab1.z), "=r"(tab1.w) : "l"(ops + i0 + 64));
        }
        if (warp == 10 && lane >= 1 && lane < M_COUNT) asm volatile("prefetch.tensormap [%0];" ::"l"(&mp.m[lane]) : "memory");
        const int xcol = 4096 + (cta - 96) * 16;
        const int base0 = helper ? (mblk0 + lane - 1) * 32 : lane == 1 ? cta * 32 : lane == 2 ? xcol : 0;
        const int base1 = lane == 1 ? krow : lane == 4 ? cta * 288 : lane == 5 ? xcol * 9 : 0;
        uint64_t pol;
        asm volatile("createpolicy.fractional.L2::evict_first.b64 %0, 1.0;" : "=l"(pol));
        const int cnt = (nops + 1 - (warp & 1)) >> 1;
        bool anchored = false;
        asm volatile("bar.sync 3, 384;" ::: "memory");
#pragma unroll 1
        for (int k = 0; k < cnt; k++) {
            if (k == 32) tab0 = tab1;
            uint4 e;
            e.x = __shfl_sync(0xffffffffu, tab0.x, k); e.y = __shfl_sync(0xffffffffu, tab0.y, k);
            e.z = __shfl_sync(0xffffffffu, tab0.z, k); e.w = __shfl_sync(0xffffffffu, tab0.w, k);
            const uint32_t bar = bars + (e.x >> 24) * 8;
            const int c0 = __shfl_sync(0xffffffffu, base0, (e.x >> 10) & 3);
            const int c1 = (e.y & 0xfff) + __shfl_sync(0xffffffffu, base1, (e.x >> 12) & 7);
            const uint32_t dst = base + (e.x & 0x3ff) * 256;
            const CUtensorMap* map = &mp.m[(e.x >> 15) & 15];
            mbar_wait(bars + ((e.y >> 12) & 0xff) * 8);
            if (lane == 0) mbar_expect(bar, ((e.x >> 19) & 15) << 10);
            if (!anchored) t_start = fu(lds_f(base + OFF_T0));
            if (e.x & (1u << 23)) {
                const int lag = (int)(now_ns() - (t_start + (e.y >> 20) * 16)) + ANCHOR_BIAS;
                if (lag > 0) t_start += (lag * ANCHOR_NUM) >> 2;
                anchored = true;
            }
            const uint32_t due = t_start + (e.y >> 20) * 16;
            unsigned n = 0;
            while (true) {
                const int lvl = min(max(PACE_MID + ((int)(now_ns() - due) >> PACE_SHIFT), 0), 7);
                if (mbar_test(bars + (__byte_perm(e.z, e.w, lvl) & 0xff) * 8)) break;
                if (++n > 64 * SPIN_LIMIT) __trap();
            }
            if (lane == 0) tma3d_hint(dst, map, c0, c1, bar, pol);
            __syncwarp();
        }
        return;
    }

    if (threadIdx.x == 32 && !helper) {
#pragma unroll
        for (int i = 0; i < K_AT_START; i++) mbar_init(bars + 8 * (U_KV + i), 1);
        mbar_init_fence();
#pragma unroll
        for (int i = 0; i < K_AT_START; i++) {
            mbar_expect(bars + 8 * (U_KV + i), CH);
            asm volatile("cp.async.bulk.shared::cluster.global.mbarrier::complete_tx::bytes [%0], [%1], %2, [%3];"
                         ::"r"(base + (S0 + i) * CH), "l"(kbytes + (size_t)krow * 256 + i * CH), "r"(CH), "r"(bars + 8 * (U_KV + i)) : "memory");
        }
    }
    if (threadIdx.x == 0) {
        const bool q1 = heavy && !helper;
        const uint32_t bb = bars + (q1 ? 8 * U_WQ : 0), dst = base + (q1 ? OFF_WQ : OFF_WMOD);
#pragma unroll
        for (int i = 0; i < 3; i++) { mbar_init(bars + 8 * i, 1); mbar_init(bars + 8 * (U_WQ + i), 1); }
        mbar_init_fence();
#pragma unroll
        for (int i = 0; i < 3; i++) {
            mbar_expect(bb + 8 * i, 12288);
            tma3d(dst + i * 12288, &mp.m[q1 ? M_WQ : M_WMOD], mblk0 * 32, i * 192, bb + 8 * i);
        }
    }
    int tid;
    asm volatile("mov.u32 %0, %tid.x;" : "=r"(tid));
    const int lane = tid & 31;
    const int warp = __shfl_sync(0xffffffffu, tid >> 5, 0);
    if (elect_one()) {
        if (warp < 7) {
            const uint32_t b0 = bars + warp * 128;
            if (warp != 0 && warp != 5) {
#pragma unroll
                for (int i = 0; i < 3; i++) mbar_init(b0 + 8 * i, 1);
            }
            if (warp != 6) {
#pragma unroll
                for (int i = 6; i < 16; i++) mbar_init(b0 + 8 * i, 1);
            }
#pragma unroll
            for (int i = 3; i < 6; i++)
                if (i >= 3 + K_AT_START || warp != 0 || helper) mbar_init(b0 + 8 * i, 1);
            mbar_arrive_if(bars + 8 * B_DONE, 1, warp == 5);
        }
        if (warp >= 6) {
#pragma unroll
            for (int i = 0; i < 16; i++) mbar_init(bars + 8 * (B_USED + (warp - 6) * 16 + i), 8);
        }
        mbar_init_fence();
    }
    sts32_if(base + OFF_T0, t_start, tid == 64);
    __syncwarp();
    asm volatile("bar.arrive 3, 384;\nbar.sync 8, 320;" ::: "memory");

    if (warp == 9) {
        if (helper) return;
        const uint32_t ep = next_epoch(gs);
        unsigned int (*cnt)[RCNT][32] = gs->cnt[ep % 3];
        if (cta < C_COUNT && lane < RCNT) st_t1(&gs->cnt[(ep + 1) % 3][cta][lane][0], 0u);
        await_count<true>(cnt[C_MOD][cta % RCNT], HINT_MOD, bars + 8 * B_GATE_MOD, lane);
#pragma unroll 1
        for (int k = 0; k < NMS; k++) {
            mbar_wait(bars + 8 * (U_KV + MS_FIRST + k * MS_STEP));
            const uint32_t tl = now_ns();
            unsigned old = 0;
            if (lane == 0 && !heavy) asm volatile("atom.relaxed.gpu.global.add.u32 %0, [%1], 1;" : "=r"(old) : "l"(cnt[C_PACE][k]) : "memory");
            old = __shfl_sync(0xffffffffu, old, 0);
            st_w1(gs->ex_pace + (k * RCNT + (lane & (RCNT - 1))) * 16, tl, ep, old == MS_RANK && lane < RCNT);
            mbar_wait(bars + 8 * (U_KV + MS_FIRST + k * MS_STEP + MS_DELAY));
            unsigned long long w = 0;
            if (lane == 0) asm volatile("atom.relaxed.gpu.global.or.b64 %0, [%1], 0;" : "=l"(w) : "l"(gs->ex_pace + (k * RCNT + cta % RCNT) * 16) : "memory");
            sts32_if(base + OFF_T0, (uint32_t)w - mp.nom[k], lane == 0 && (uint32_t)(w >> 32) == ep);
            __syncwarp();
        }
        mbar_wait(bars + 8 * (U_KV + 63));
        {
            float v[8];
            poll_lines<8, 256, true>(gs->ex_o + (cta & ~7) * 256 + (cta & 7) * 32 + lane, v, 1 + ep % 3);
            const float o0 = (v[0] + v[1]) + (v[2] + v[3]), o1 = (v[4] + v[5]) + (v[6] + v[7]);
            const float r = __shfl_xor_sync(0xffffffffu, (lane & 1) ? o0 : o1, 1);
            const int wi = lane >> 1;
            sts32_if(base + OFF_OB + ((lane & 1) * 16 + (wi & 3) * 4 + (wi >> 2)) * 4, (lane & 1) ? pack2(r, o1) : pack2(o0, r), true);
        }
        asm volatile("bar.arrive 4, 320;" ::: "memory");
#pragma unroll 1
        for (int k = cta < NRED ? C_AO : C_X1; k <= C_X1; k++)
            await_count<false>(cnt[k][cta % (k ? RCNT : RCNT0)], k ? HINT_X1 : HINT_AO, bars + 8 * (B_GATE_AO + k), lane);
        asm volatile("bar.sync 6, 320;" ::: "memory");
#pragma unroll
        for (int h = 0; h < 2; h++) {
            if (h == 0 || heavy) {
                const int ci = h * 32 + (h ? lane & 15 : lane);
                float4 u[9];
#pragma unroll
                for (int w = 0; w < 9; w++) u[w] = lds_f4(base + OFF_SC + (w * 48 + ci) * 16);
                float4 s;
                s.x = (((u[0].x + u[1].x) + (u[2].x + u[3].x)) + ((u[4].x + u[5].x) + (u[6].x + u[7].x))) + u[8].x;
                s.y = (((u[0].y + u[1].y) + (u[2].y + u[3].y)) + ((u[4].y + u[5].y) + (u[6].y + u[7].y))) + u[8].y;
                s.z = (((u[0].z + u[1].z) + (u[2].z + u[3].z)) + ((u[4].z + u[5].z) + (u[6].z + u[7].z))) + u[8].z;
                s.w = (((u[0].w + u[1].w) + (u[2].w + u[3].w)) + ((u[4].w + u[5].w) + (u[6].w + u[7].w))) + u[8].w;
                float g0 = rbf(s.x), g1 = rbf(s.y);
                g0 = g0 * (g0 > 0.f ? 1.f : 0.f);
                g1 = g1 * (g1 > 0.f ? 1.f : 0.f);
                const uint32_t hp = pack2(g0 * rbf(s.z), g1 * rbf(s.w));
                sts16(base + OFF_HH + ci * 2, hp);
                sts16(base + OFF_HH + 128 + ci * 2, hp >> 16);
            }
        }
        asm volatile("bar.arrive 7, 320;" ::: "memory");
        return;
    }

    const int kvh = cta >> 3, bat = (cta >> 2) & 1;
    const int nmod = helper ? 3 : heavy ? 0 : 1;
    const int g = lane >> 2, t = lane & 3;
    const int fb = g & 1;
    const int col0 = warp * 64 + (g >> 1) * 16 + 2 * t;
    const bool reducer = cta < NRED;
    const int rcol = (reducer ? cta : 0) * 16 + (lane & 15), rb_ = lane >> 4;
    const uint32_t s_sc = base + OFF_SC, s_stats = base + OFF_ST, s_r2 = base + OFF_R2;
    const uint32_t ca_ = ldg32(cvec + fb * DM + col0), cb_ = ldg32(cvec + fb * DM + col0 + 8);
    const uint32_t xa = ldg32(x + fb * DM + col0), xb = ldg32(x + fb * DM + col0 + 8);
    const uint32_t tag = next_epoch(gs);
    const float xr = bf_sel(ldg32(x + rb_ * DM + (rcol & ~1)), lane & 1);
    unsigned int (*cnt)[RCNT][32] = gs->cnt[tag % 3];

    float y[4] = {bf_lo(xa), bf_hi(xa), bf_lo(xb), bf_hi(xb)};
    {
        float cv[4] = {bf_lo(ca_), bf_hi(ca_), bf_lo(cb_), bf_hi(cb_)};
#pragma unroll
        for (int i = 0; i < 4; i++) cv[i] = cv[i] / (1.f + expf(-cv[i]));
        const uint32_t s01 = pack2(cv[0], cv[1]), s23 = pack2(cv[2], cv[3]);
        ln_part1(y, s_stats, warp, lane);
#pragma unroll 1
        for (int m = 0; m < nmod; m++)
            gemv32(base + OFF_WMOD + m * 36864, bars + 8 * (m == 1 ? U_WQ : m == 2 ? 3 : 0), s01, s23, s_sc + m * 2304, warp);
    }
    bar_comp();
    if (warp < nmod) {
        const float2 s2 = sum9(s_sc + warp * 2304 + lane * 8);
#pragma unroll
        for (int r = 0; r < REP1; r++) st_w1(gs->ex_mod + r * 6 * DM + (mblk0 + warp) * 32 + lane, pack2(s2.x, s2.y), tag, true);
        announce(cnt[C_MOD][lane & (RCNT - 1)], cta < 36 && lane < RCNT);
    }
    if (helper) return;
    mbar_arrive_if(bars + 8 * B_MODFREE, 1, tid == 256);
    ln_part2(y, s_stats, lane);
    const int rr = (lane & 7) + ((lane >> 4) << 3), hi8 = (lane >> 3) & 1;
    float cbv[4], sbv[4], gar, gbr;
    const int zoff[1] = {0};
    {
        const unsigned long long* mod = gs->ex_mod + (cta % REP1) * 6 * DM;
        const int moff[4] = {0, 8, DM, DM + 8};
        uint32_t v[8];
        mbar_wait(bars + 8 * B_GATE_MOD);
        poll2<4, false>(mod + col0, moff, v, tag, true);
        float h[4];
#pragma unroll
        for (int i = 0; i < 4; i++) h[i] = rbf(y[i] * rbf(1.f + bf_sel(v[4 + i], fb))) + bf_sel(v[i], fb);
        gemv32(base + OFF_WQ, bars + 8 * U_WQ, pack2(h[0], h[1]), pack2(h[2], h[3]), s_sc + 2304, warp);
        bar_comp();
        if (warp == 0) {
            const float2 s2 = sum9(s_sc + 2304 + lane * 8);
            const float o0 = __shfl_xor_sync(0xffffffffu, s2.x, 1), o1 = __shfl_xor_sync(0xffffffffu, s2.y, 1);
            st_w1(gs->ex_q + (lane & 1) * 2048 + cta * 16 + (lane >> 1), (lane & 1) ? pack2(o1, s2.y) : pack2(s2.x, o0), tag, true);
        }
        mbar_arrive_if(bars + 8 * B_WQFREE, 1, tid == 256);
        poll2<4, false>(mod + 3 * DM + col0, moff, v, tag, true);
#pragma unroll
        for (int i = 0; i < 4; i++) { sbv[i] = bf_sel(v[i], fb); cbv[i] = rbf(1.f + bf_sel(v[4 + i], fb)); }
        if (warp < 2) {
            uint32_t qv[2];
            poll2<1, true>(gs->ex_q + bat * 2048 + kvh * 128 + tid * 2, zoff, qv, tag, true);
            sts64_if(base + OFF_Q + tid * 8, qv[0], qv[1], true);
        }
        bar_comp();
        const int goff[2] = {0, 3 * DM};
        uint32_t gv[4];
        poll2<2, false>(mod + 2 * DM + (rcol & ~1), goff, gv, tag, reducer && warp == RED_WARP);
        gar = bf_sel((lane & 1) ? gv[1] : gv[0], rb_);
        gbr = bf_sel((lane & 1) ? gv[3] : gv[2], rb_);
    }

    const int line0 = rr * 9 + warp;
    const uint32_t rowa = base + line0 * 128;
    const uint32_t lsw = line0 & 7;
    uint32_t wf[4][4][4];
    const uint32_t tg0 = 1 + tag % 3, tg1 = 1 + (2 * (tag % 3)) % 3, tg2 = 1 + (2 * (tag % 3) + 1) % 3;
    unsigned long long* x1dst = gs->ex_x1 + ((lane >> 3) & 1) * 288 + cta * 8 + rb_ * 4 + ((lane >> 1) & 3);
    uint32_t* part = gs->ex_part + cta * (DM * 2) + (warp * 4 + t) * 32 + g * 4;
    const bool x1pub = reducer && warp == RED_WARP && (lane & 1) == 0;
    auto prewrite = [&]() { st_t4(part, 0u, 0u, 0u, 0u); st_w1(x1dst, 0u, 0u, x1pub); };
    auto publish = [&](const float (&acc)[4][4], uint32_t tg) {
        st_t4(part, tagf(sel4(t, acc[0][0], acc[1][0], acc[2][0], acc[3][0]), tg), tagf(sel4(t, acc[0][1], acc[1][1], acc[2][1], acc[3][1]), tg),
              tagf(sel4(t, acc[0][2], acc[1][2], acc[2][2], acc[3][2]), tg), tagf(sel4(t, acc[0][3], acc[1][3], acc[2][3], acc[3][3]), tg));
    };

    if (warp < 8) {
        uint4 qf[4];
#pragma unroll
        for (int j = 0; j < 4; j++) qf[j] = lds128(base + OFF_Q + (g & 1) * 256 + ((j ^ ((g >> 1) & 1)) << 6) + t * 16);
        float mx0 = -INFINITY, mx1 = -INFINITY;
        const uint32_t rowoff = base + ((warp & 1) * 16 + g) * 256 + t * 16;
        const uint32_t sw = (g & 1) << 6;
        const bool valid = (g & 1) == (t & 1);
        uint32_t scp = s_sc + (warp * 16 + g + ((t & 2) << 2)) * 4;
#pragma unroll 1
        for (int c = warp >> 1; c < 32; c += 4) {
            const int s = c + S0 >= NS ? c + S0 - NS : c + S0;
            mbar_wait(bars + 8 * (U_KV + c));
            const uint32_t a0 = rowoff + s * CH;
            float acc[4] = {}, acc2[4] = {};
#pragma unroll
            for (int j = 0; j < 4; j++) {
                const uint32_t o = (j << 6) ^ sw;
                const uint4 lo = lds128(a0 + o), hi = lds128(a0 + 2048 + o);
                mma(acc, lo.x, hi.x, lo.y, hi.y, qf[j].x, qf[j].y);
                mma(acc2, lo.z, hi.z, lo.w, hi.w, qf[j].z, qf[j].w);
            }
            __syncwarp();
            mbar_arrive_if(bars + 8 * (B_USED + c), 4, lane == 0);
            float u0 = (t & 2) ? acc[2] + acc2[2] : acc[0] + acc2[0];
            float u1 = (t & 2) ? acc[3] + acc2[3] : acc[1] + acc2[1];
            u0 = rbf(rbf(u0) * 0.08838834764831845f);
            u1 = rbf(rbf(u1) * 0.08838834764831845f);
            sts32_if(scp, fu(u0), valid);
            sts32_if(scp + 4096, fu(u1), valid);
            mx0 = valid ? fmaxf(mx0, u0) : mx0;
            mx1 = valid ? fmaxf(mx1, u1) : mx1;
            scp += 512;
        }
#pragma unroll
        for (int m = 1; m < 32; m <<= 1) {
            mx0 = fmaxf(mx0, __shfl_xor_sync(0xffffffffu, mx0, m));
            mx1 = fmaxf(mx1, __shfl_xor_sync(0xffffffffu, mx1, m));
        }
        sts64_if(s_stats + warp * 8, fu(mx0), fu(mx1), lane == 0);
        bar_256();
        const int uh = g & 1;
        float mloc = -INFINITY;
#pragma unroll
        for (int w = 0; w < 8; w++) mloc = fmaxf(mloc, lds_f(s_stats + (2 * w + uh) * 4));
        float e[8];
#pragma unroll
        for (int i = 0; i < 4; i++) {
            const float2 v = lds_f2(s_sc + (uh * 1024 + (tid >> 3) * 32 + 2 * t + i * 8) * 4);
            e[2 * i] = __expf(v.x - mloc);
            e[2 * i + 1] = __expf(v.y - mloc);
        }
        float l = ((e[0] + e[1]) + (e[2] + e[3])) + ((e[4] + e[5]) + (e[6] + e[7]));
        l += __shfl_xor_sync(0xffffffffu, l, 1);
        l += __shfl_xor_sync(0xffffffffu, l, 2);
        l += __shfl_xor_sync(0xffffffffu, l, 8);
        l += __shfl_xor_sync(0xffffffffu, l, 16);
        sts32_if(s_stats + (16 + 2 * warp + uh) * 4, fu(l), (lane & ~4) == 0);
        bar_256();
        if (warp == 0) {
            float lt = 0.f;
#pragma unroll
            for (int w = 0; w < 8; w++) lt += lds_f(s_stats + (16 + 2 * w + uh) * 4);
            st_w2(gs->ex_ml + cta * 4 + uh * 2, fu(mloc), fu(lt), tag, (lane & ~4) == 0);
            uint32_t ml[2];
            poll2<1, true>(gs->ex_ml + ((cta & ~3) + t) * 4 + uh * 2, zoff, ml, tag, true);
            const float ms = uf(ml[0]), ls = uf(ml[1]);
            float M = fmaxf(ms, __shfl_xor_sync(0xffffffffu, ms, 1));
            M = fmaxf(M, __shfl_xor_sync(0xffffffffu, M, 2));
            float L = ls * __expf(ms - M);
            L += __shfl_xor_sync(0xffffffffu, L, 1);
            L += __shfl_xor_sync(0xffffffffu, L, 2);
            sts32_if(s_stats + (32 + uh) * 4, fu(__expf(mloc - M) / L), (lane & ~4) == 0);
        }
        bar_256();
        const float f = lds_f(s_stats + (32 + uh) * 4);
        sts128_if(base + OFF_P + tid * 16, pack2(e[0] * f, e[1] * f), pack2(e[2] * f, e[3] * f), pack2(e[4] * f, e[5] * f),
                  pack2(e[6] * f, e[7] * f), true);
        bar_256();

        float acc[4] = {}, acc2[4] = {};
        const int cc = (warp & 3) * 2 + hi8;
        const uint32_t voff = base + (warp >> 2) * (CH / 2) + rr * 128 + ((cc ^ (lane & 7)) << 4);
        uint32_t poff = base + OFF_P + (g & 1) * 64 + t * 16;
        uint32_t* odst = gs->ex_o + cta * 256 + (t & 1) * 128 + warp * 16 + ((t & 2) << 2) + g;
#pragma unroll 1
        for (int c = 32; c < 64; c++) {
            const int s = c + S0 >= 2 * NS ? c + S0 - 2 * NS : c + S0 - NS;
            if (c == PREWRITE_AT) { st_t1(odst, 0u); prewrite(); }
            const uint4 p0 = lds128(poff);
            poff += 128;
            mbar_wait(bars + 8 * (U_KV + c));
            uint32_t a[4], a2[4];
            ldsm4t(a, voff + s * CH);
            ldsm4t(a2, voff + s * CH + 2048);
            mma(acc, a, p0.x, p0.y);
            mma(acc2, a2, p0.z, p0.w);
            __syncwarp();
            mbar_arrive_if(bars + 8 * (B_USED + c), 1, lane == 0);
        }
        st_t1(odst, tagf(sel4(t, acc[0] + acc2[0], acc[1] + acc2[1], acc[2] + acc2[2], acc[3] + acc2[3]), tg0));
    } else {
        mbar_wait(bars + 8 * (U_KV + PREWRITE_AT));
        prewrite();
    }
    {
#pragma unroll
        for (int ks = 0; ks < 2; ks++) {
            mbar_wait(bars + 8 * (U_WO + 2 * ks)); mbar_wait(bars + 8 * (U_WO + 2 * ks + 1));
#pragma unroll
            for (int mt = 0; mt < 4; mt++) ldsm4t(wf[ks][mt], rowa + OFF_WO + ks * 18432 + (((mt * 2 + hi8) ^ lsw) << 4));
        }
        asm volatile("bar.sync 4, 320;" ::: "memory");
        const uint4 ob = lds128(base + OFF_OB + fb * 64 + t * 16);
        float acc[4][4] = {};
#pragma unroll
        for (int mt = 0; mt < 4; mt++) mma(acc[mt], wf[0][mt], ob.x, ob.y);
#pragma unroll
        for (int mt = 0; mt < 4; mt++) mma(acc[mt], wf[1][mt], ob.z, ob.w);
        publish(acc, tg1);
        announce(cnt[C_AO][lane & (RCNT - 1)], warp == 8 && lane < RCNT0);
    }
    const uint32_t gub = bars + 8 * (U_GU + 2 * (warp / 3));
    const uint32_t gxb = heavy ? bars + 8 * (U_GX + 2 * (warp / 3)) : gub;
    uint32_t dn[3][4][4];
    auto load_gu = [&]() {
        const uint32_t rb = base + OFF_GU + hi8 * 36864 + (warp * 64 + rr) * 64;
#pragma unroll
        for (int ks = 0; ks < 4; ks++)
#pragma unroll
            for (int j = 0; j < 4; j++) ldsm4t(wf[ks][j], rb + ks * 1024 + ((j ^ ((rr >> 1) & 3)) << 4));
        if (heavy) {
            const uint32_t rx = base + OFF_GX + hi8 * 18432 + (warp * 64 + rr) * 32;
#pragma unroll
            for (int ks = 0; ks < 4; ks++)
#pragma unroll
                for (int j = 0; j < 2; j++) ldsm4t(dn[1 + j][ks], rx + ks * 512 + ((j ^ ((rr >> 2) & 1)) << 4));
        }
    };
    auto load_dn = [&](int ks) {
#pragma unroll
        for (int mt = 0; mt < 4; mt++) ldsm4t(dn[ks][mt], rowa + OFF_DN + ks * 18432 + (((mt * 2 + hi8) ^ lsw) << 4));
    };
    auto dn_in = [&](int ks) {
        return __all_sync(0xffffffffu, mbar_test(bars + 8 * (U_DN + 2 * ks)) && mbar_test(bars + 8 * (U_DN + 2 * ks + 1)));
    };
    bool have_gu = false, have_dn = false;
    auto try_gu = [&]() {
        if (!have_gu && __all_sync(0xffffffffu, mbar_test(gxb + 8) && mbar_test(gxb) && mbar_test(gub + 8) && mbar_test(gub))) {
            load_gu();
            have_gu = true;
        }
    };
    auto gate = [&](uint32_t gb) {
        unsigned n = 0;
        while (true) {
            try_gu();
            if (__all_sync(0xffffffffu, have_gu ? mbar_try(gb) : mbar_test(gb))) break;
            if (++n > 64 * SPIN_LIMIT) __trap();
        }
    };
    const uint32_t* rsrc = gs->ex_part + (warp & 7) * 16 * (DM * 2) + cta * 32 + lane;
    float x1r = 0.f;
    if (reducer) {
        gate(bars + 8 * B_GATE_AO);
        if (warp < 8) reduce_part1(rsrc, s_r2, warp, lane, tg1);
        bar_comp();
        if (warp == RED_WARP) {
            x1r = rbf(xr + rbf(gar * rbf(reduce_part2(s_r2, lane))));
            const float other = __shfl_xor_sync(0xffffffffu, x1r, 1);
            st_w1(x1dst, pack2(x1r, other), tag, x1pub);
            announce(cnt[C_X1][lane & (RCNT - 1)], lane < RCNT);
        }
    }
    gate(bars + 8 * B_GATE_X1);
    {
        unsigned long long w0, w1;
        unsigned n = 0;
        while (true) {
            asm volatile("ld.relaxed.gpu.global.b64 %0, [%1];" : "=l"(w0) : "l"(gs->ex_x1 + tid) : "memory");
            asm volatile("ld.relaxed.gpu.global.b64 %0, [%1];" : "=l"(w1) : "l"(gs->ex_x1 + 288 + tid) : "memory");
            try_gu();
            if (!have_dn && dn_in(0)) { load_dn(0); have_dn = true; }
            if (__all_sync(0xffffffffu, (uint32_t)(w0 >> 32) == tag && (uint32_t)(w1 >> 32) == tag)) break;
            if (++n > SPIN_LIMIT) __trap();
        }
        y[0] = bf_lo((uint32_t)w0); y[1] = bf_hi((uint32_t)w0); y[2] = bf_lo((uint32_t)w1); y[3] = bf_hi((uint32_t)w1);
        ln_part1(y, s_stats, warp, lane);
        if (!have_gu) { mbar_wait(gub); mbar_wait(gub + 8); mbar_wait(gxb); mbar_wait(gxb + 8); load_gu(); }
        bar_comp();
        ln_part2(y, s_stats, lane);
        uint32_t bfr[4][2];
        spread_b(bfr, pack2(rbf(y[0] * cbv[0]) + sbv[0], rbf(y[1] * cbv[1]) + sbv[1]),
                 pack2(rbf(y[2] * cbv[2]) + sbv[2], rbf(y[3] * cbv[3]) + sbv[3]), lane);
        const uint32_t red = s_sc + (warp * 48 + g + t * 8) * 16;
        float acc[4][4] = {};
#pragma unroll
        for (int ks = 0; ks < 4; ks++)
#pragma unroll
            for (int j = 0; j < 4; j++) mma(acc[j], wf[ks][j], bfr[ks][0], bfr[ks][1]);
        if (heavy) {
            float ax[2][4] = {};
#pragma unroll
            for (int ks = 0; ks < 4; ks++)
#pragma unroll
                for (int j = 0; j < 2; j++) mma(ax[j], dn[1 + j][ks], bfr[ks][0], bfr[ks][1]);
            sts128_if(red + 512, fu(t ? ax[1][0] : ax[0][0]), fu(t ? ax[1][1] : ax[0][1]), fu(t ? ax[1][2] : ax[0][2]),
                      fu(t ? ax[1][3] : ax[0][3]), t < 2);
        }
        sts128_if(red, fu(sel4(t, acc[0][0], acc[1][0], acc[2][0], acc[3][0])), fu(sel4(t, acc[0][1], acc[1][1], acc[2][1], acc[3][1])),
                  fu(sel4(t, acc[0][2], acc[1][2], acc[2][2], acc[3][2])), fu(sel4(t, acc[0][3], acc[1][3], acc[2][3], acc[3][3])), true);
        asm volatile("bar.arrive 6, 320;" ::: "memory");
    }
    {
        bool got[3];
#pragma unroll
        for (int ks = 0; ks < 3; ks++) {
            got[ks] = ks == 0 && have_dn;
            if (!got[ks] && (ks < 2 || heavy) && dn_in(ks)) { load_dn(ks); got[ks] = true; }
        }
        asm volatile("bar.sync 7, 320;" ::: "memory");
        uint32_t hb[6];
#pragma unroll
        for (int i = 0; i < 6; i++) hb[i] = fu(lds_f(base + OFF_HH + (fb * 32 + t + i * 4) * 4));
        float acc[4][4] = {};
#pragma unroll
        for (int ks = 0; ks < 3; ks++) {
            if (ks < 2 || heavy) {
                if (!got[ks]) {
                    mbar_wait(bars + 8 * (U_DN + 2 * ks)); mbar_wait(bars + 8 * (U_DN + 2 * ks + 1));
                    load_dn(ks);
                }
#pragma unroll
                for (int mt = 0; mt < 4; mt++) mma(acc[mt], dn[ks][mt], hb[2 * ks], hb[2 * ks + 1]);
            }
        }
        publish(acc, tg2);
    }
    if (reducer) {
        if (warp < 8) reduce_part1(rsrc, s_r2, warp, lane, tg2);
        bar_comp();
        if (warp == RED_WARP) {
            const float r = x1r + rbf(gbr * rbf(reduce_part2(s_r2, lane)));
            const float other = __shfl_xor_sync(0xffffffffu, r, 1);
            if (x1pub) *reinterpret_cast<uint32_t*>(out + rb_ * DM + rcol) = pack2(r, other);
            if (cta == 0 && lane == 0) st_t1(&gs->epoch, tag);
        }
    }
}

typedef CUresult (*EncodeFn)(CUtensorMap*, CUtensorMapDataType, cuuint32_t, void*, const cuuint64_t*, const cuuint64_t*,
                             const cuuint32_t*, const cuuint32_t*, CUtensorMapInterleave, CUtensorMapSwizzle,
                             CUtensorMapL2promotion, CUtensorMapFloatOOBfill);

void make_map(EncodeFn enc, CUtensorMap* m, const void* p, uint64_t cols, uint64_t rows, uint32_t bc, uint32_t br,
              CUtensorMapSwizzle sw, CUtensorMapL2promotion prom, bool split_halves = false) {
    cuuint64_t gd[3] = {split_halves ? cols / 2 : cols, rows, split_halves ? 2u : 1u};
    cuuint64_t gs[2] = {cols * 2, split_halves ? cols : cols * 2 * rows};
    cuuint32_t bx[3] = {bc, br, split_halves ? 2u : 1u};
    cuuint32_t es[3] = {1, 1, 1};
    enc(m, CU_TENSOR_MAP_DATA_TYPE_BFLOAT16, 3, const_cast<void*>(p), gd, gs, bx, es, CU_TENSOR_MAP_INTERLEAVE_NONE, sw, prom,
        CU_TENSOR_MAP_FLOAT_OOB_FILL_NONE);
}

void build_ops(uint4* list, bool heavy, int* nom) {
    constexpr int NMAX = NOPS_HEAVY + NPRE;
    uint4 op[NMAX];
    int order[NMAX], n = 0;
    for (int u = 0; u < 3; u++) order[n++] = heavy ? U_WQ + u : u;
    for (int u = U_KV; u < U_KV + K_AT_START; u++) order[n++] = u;
    if (!heavy) for (int u = 0; u < 3; u++) order[n++] = U_WQ + u;
    for (int u = U_KV + K_AT_START; u < U_WO; u++) order[n++] = u;
    const int n_v = n;
    for (int k = 0; k < 4; k++) order[n++] = U_WO + k;
    for (int k = 0; k < 3; k++) {
        order[n++] = U_GU + 2 * k; order[n++] = U_GU + 2 * k + 1;
        if (heavy) { order[n++] = U_GX + 2 * k; order[n++] = U_GX + 2 * k + 1; }
    }
    for (int k = 0; k < (heavy ? 6 : 4); k++) order[n++] = U_DN + k;
    int kb[NMAX], win[NMAX], cum[NMAX + 1];
    cum[0] = 0;
    for (int i = 0; i < n; i++) {
        const int u = order[i];
        int dst, sel0 = 0, sel1 = 0, row = 0, map, spb = -1;
        win[i] = WIN_TAIL;
        if (u < U_KV || (u >= U_WQ && u < U_GX)) {
            const int k = u < U_KV ? u : u - U_WQ + 3;
            map = k < 3 ? M_WMOD : M_WQ; dst = OFF_WMOD + k * 12288; sel0 = 1; row = (k % 3) * 192; kb[i] = 12;
            spb = B_DONE; win[i] = WIN_MID;
        } else if (u < U_WO) {
            const int c = u - U_KV, slot = (c + S0) % NS;
            map = c < 32 ? M_K : M_V; dst = slot * CH; sel1 = 1; row = ((c & 31) >> 1) * 256 + (c & 1) * 32; kb[i] = 8;
            spb = c >= NS ? B_USED + c - NS : (slot >= 9 && slot <= 13) ? B_WQFREE : (slot >= 5 && slot < 9) ? B_MODFREE : B_DONE;
            win[i] = c < 64 - END_CHUNKS ? WIN_MID : WIN_END;
        } else if (u < U_GU) {
            const int k = u - U_WO;
            map = M_WO; dst = OFF_WO + k * 9216; sel1 = 4; row = k * 72; kb[i] = 9; win[i] = WIN_END;
        } else if (u < U_WQ) {
            const int k = u - U_GU;
            map = M_GATE + (k & 1); dst = OFF_GU + (k & 1) * 36864 + (k >> 1) * 12288; sel0 = 1; row = (k >> 1) * 192; kb[i] = 12;
        } else if (u < U_DN) {
            const int k = u - U_GX;
            map = M_GATEX + (k & 1); dst = OFF_GX + (k & 1) * 18432 + (k >> 1) * 6144; sel0 = 2; row = (k >> 1) * 192; kb[i] = 6;
        } else {
            const int k = u - U_DN;
            map = M_DN; dst = OFF_DN + k * 9216; kb[i] = 9; win[i] = WIN_LAST;
            if (k < 4) { sel1 = 4; row = k * 72; } else { sel1 = 5; row = (k - 4) * 72; }
        }
        if (heavy && i >= n_v) win[i] += WIN_HEAVY_EXTRA;
        if (spb < 0) spb = B_USED + 64 - NS + ((dst + kb[i] * 1024 - 1) >> 13);
        cum[i + 1] = cum[i] + kb[i];
        op[i].x = (dst >> 8) | (sel0 << 10) | (sel1 << 12) | (map << 15) | (kb[i] << 19) | ((unsigned)u << 24) |
                  ((i == n_v - ANCHOR_BACK || i == n_v - ANCHOR_BACK + 1) ? 1u << 23 : 0u);
        op[i].y = row | (spb << 12);
    }
    const double tv = heavy ? PACE_TV_HEAVY : PACE_TV;
    for (int i = 0; i < n; i++) {
        double due = i <= n_v ? PACE_T0 + (tv - PACE_T0) * cum[i] / cum[n_v] : tv + (PACE_TE - tv) * (cum[i] - cum[n_v]) / (cum[n] - cum[n_v]);
        if (due < 0) due = 0;
        op[i].y |= (unsigned)(due / 16) << 20;
        for (int k = 0; k < NMS; k++)
            if (nom && order[i] == U_KV + MS_FIRST + k * MS_STEP + 5) nom[k] = (int)due + MS_BIAS;
        unsigned long long lv = 0;
        for (int l = 0; l < 8; l++) {
            int w = win[i] + (l - PACE_MID) * PACE_STEP, wd = B_DONE;
            if (w < PACE_WMIN) w = PACE_WMIN;
            if (w > PACE_WMAX) w = PACE_WMAX;
            if (i >= n_v && w > win[i] + TAIL_UP) w = win[i] + TAIL_UP;
            for (int j = i - 1; j >= 0; j--)
                if (cum[i + 1] - cum[j] > w) { wd = order[j]; break; }
            lv |= (unsigned long long)wd << (8 * l);
        }
        op[i].z = (unsigned)lv;
        op[i].w = (unsigned)(lv >> 32);
        if (i >= NPRE) list[i - NPRE] = op[i];
    }
}

}

extern "C" void kernel_launch(void* const* d_in, const int* in_sizes, int n_in, void* d_out, int out_size) {
    (void)in_sizes; (void)n_in; (void)out_size;
    const __nv_bfloat16* x = (const __nv_bfloat16*)d_in[0];
    const __nv_bfloat16* kc = (const __nv_bfloat16*)d_in[1];
    const __nv_bfloat16* vc = (const __nv_bfloat16*)d_in[2];
    const __nv_bfloat16* wq = (const __nv_bfloat16*)d_in[3];
    const __nv_bfloat16* wo = (const __nv_bfloat16*)d_in[4];
    const __nv_bfloat16* wg = (const __nv_bfloat16*)d_in[6];
    const __nv_bfloat16* wu = (const __nv_bfloat16*)d_in[7];
    const __nv_bfloat16* wd = (const __nv_bfloat16*)d_in[8];
    const __nv_bfloat16* cv = (const __nv_bfloat16*)d_in[9];
    const __nv_bfloat16* wm = (const __nv_bfloat16*)d_in[10];

    EncodeFn enc = nullptr;
    cudaDriverEntryPointQueryResult qr;
    cudaGetDriverEntryPoint("cuTensorMapEncodeTiled", (void**)&enc, cudaEnableDefault, &qr);
    cudaFuncSetAttribute(fused_block_kernel, cudaFuncAttributeMaxDynamicSharedMemorySize, SMEM_BYTES);
    Params mp;
    const CUtensorMapL2promotion P128 = CU_TENSOR_MAP_L2_PROMOTION_L2_128B, P256 = CU_TENSOR_MAP_L2_PROMOTION_L2_256B;
    make_map(enc, &mp.m[M_WMOD], wm, 6 * DM, DM, 32, 192, CU_TENSOR_MAP_SWIZZLE_64B, P128);
    make_map(enc, &mp.m[M_WQ], wq, 4096, DM, 32, 192, CU_TENSOR_MAP_SWIZZLE_64B, P128);
    make_map(enc, &mp.m[M_K], kc, 128, (uint64_t)2 * 16 * SK, 128, 32, CU_TENSOR_MAP_SWIZZLE_NONE, P256);
    make_map(enc, &mp.m[M_V], vc, 128, (uint64_t)2 * 16 * SK, 64, 32, CU_TENSOR_MAP_SWIZZLE_128B, P256, true);
    make_map(enc, &mp.m[M_WO], wo, 64, 4096 * 9, 64, 72, CU_TENSOR_MAP_SWIZZLE_128B, P256);
    make_map(enc, &mp.m[M_DN], wd, 64, FF * 9, 64, 72, CU_TENSOR_MAP_SWIZZLE_128B, P256);
    make_map(enc, &mp.m[M_GATE], wg, FF, DM, 32, 192, CU_TENSOR_MAP_SWIZZLE_64B, P128);
    make_map(enc, &mp.m[M_UP], wu, FF, DM, 32, 192, CU_TENSOR_MAP_SWIZZLE_64B, P128);
    make_map(enc, &mp.m[M_GATEX], wg, FF, DM, 16, 192, CU_TENSOR_MAP_SWIZZLE_32B, P128);
    make_map(enc, &mp.m[M_UPX], wu, FF, DM, 16, 192, CU_TENSOR_MAP_SWIZZLE_32B, P128);
    build_ops(mp.op, false, mp.nom);
    build_ops(mp.op + NOPS_LIGHT, true, nullptr);
    for (int i = 3; i < 9; i++) {
        const int blk = i / 3, bar = (blk == 1 ? U_WQ : 3) + i % 3;
        mp.op[NOPS_LIGHT + NOPS_HEAVY + i - 3] =
            make_uint4(((OFF_WMOD + i * 12288) >> 8) | ((blk + 1) << 10) | (M_WMOD << 15) | (12 << 19) | (bar << 24),
                       (i % 3) * 192 | (B_DONE << 12), B_DONE * 0x01010101u, B_DONE * 0x01010101u);
    }
    Scratch* gs = nullptr;
    cudaGetSymbolAddress((void**)&gs, g_scratch);
    fused_block_kernel<<<NCTA + NHELP, NTHR, SMEM_BYTES>>>(x, cv, (__nv_bfloat16*)d_out, gs, (const char*)kc, mp);
}
```

```cpp
#include <cuda_runtime.h>
#include <cuda.h>
#include <cuda_bf16.h>
#include <stdint.h>

namespace {

constexpr int DM = 576;
constexpr int FF = 4608;
constexpr int SK = 32768;
constexpr int WIN = 4096;
constexpr int NCTA = 128;
constexpr int NHELP = 4;
constexpr int NTHR = 384;
constexpr int NRED = 36;
constexpr int RED_WARP = 8;

constexpr int WIN_MID = 40, WIN_END = 48, WIN_TAIL = 32, WIN_LAST = 36;
constexpr int WIN_HEAVY_EXTRA = 12, END_CHUNKS = 8;
constexpr int PACE_T0 = -500, PACE_TV = 22700, PACE_TV_HEAVY = 22500, PACE_TE = 29200;
constexpr int PACE_MID = 3, PACE_STEP = 8, PACE_SHIFT = 8;
constexpr int PACE_WMIN = 18, PACE_WMAX = 64, TAIL_UP = 8;
constexpr int ANCHOR_BACK = 8, ANCHOR_BIAS = 650;
constexpr int NMS = 4, MS_FIRST = 10, MS_STEP = 13, MS_DELAY = 5, MS_RANK = 47;
constexpr int K_AT_START = 2;
constexpr int REP1 = 8;
constexpr int RCNT = 8, RCNT0 = 4;
constexpr unsigned HINT_MOD = 36, HINT_AO = 112, HINT_X1 = 28;
constexpr int PREWRITE_AT = 54;
constexpr int SLEEP_NS = 100;
constexpr unsigned SPIN_LIMIT = 1u << 22;

constexpr int CH = 8192;
constexpr int NS = 26;
constexpr int S0 = 14;
constexpr int OFF_WMOD = 40960;
constexpr int OFF_WQ = 77824;
constexpr int OFF_WO = 0;
constexpr int OFF_GU = 36864;
constexpr int OFF_GX = 110592;
constexpr int OFF_DN = 147456;
constexpr int OFF_SC = NS * CH;
constexpr int OFF_P = OFF_SC + 8192;
constexpr int OFF_Q = OFF_P + 4096;
constexpr int OFF_ST = OFF_Q + 512;
constexpr int OFF_HH = OFF_ST + 256;
constexpr int OFF_R2 = OFF_HH + 256;
constexpr int OFF_OB = OFF_R2 + 1024;
constexpr int OFF_T0 = OFF_OB + 128;
constexpr int OFF_BAR = OFF_T0 + 128;
constexpr int SMEM_BYTES = OFF_BAR + 192 * 8 + 1024;
static_assert(SMEM_BYTES <= 232448, "smem");

constexpr int U_KV = 3;
constexpr int U_WO = 67;
constexpr int U_GU = 71;
constexpr int U_WQ = 80;
constexpr int U_GX = 83;
constexpr int U_DN = 89;
constexpr int B_DONE = 95;
constexpr int B_MODFREE = 96, B_WQFREE = 97;
constexpr int B_GATE_AO = 98, B_GATE_X1 = 99, B_GATE_MOD = 100;
constexpr int B_USED = 128;

enum { M_WMOD, M_WQ, M_K, M_V, M_WO, M_DN, M_GATE, M_UP, M_GATEX, M_UPX, M_COUNT };
constexpr int NPRE = 3 + K_AT_START;
constexpr int NOPS_LIGHT = 84 - NPRE, NOPS_HEAVY = 89 - NPRE, NOPS_HELP = 6;
struct Params { CUtensorMap m[M_COUNT]; uint4 op[NOPS_LIGHT + NOPS_HEAVY + NOPS_HELP]; int nom[NMS]; };

static_assert(sizeof(Params) + 64 <= 4096 && NMS <= RCNT, "kernel parameters");

enum { C_AO, C_X1, C_PACE, C_MOD, C_COUNT };
struct __align__(128) Scratch {
    unsigned int epoch;
    unsigned int pad[31];
    unsigned int cnt[3][C_COUNT][RCNT][32];
    unsigned long long ex_mod[REP1 * 6 * DM];
    unsigned long long ex_q[2 * 2048];
    unsigned long long ex_x1[DM];
    unsigned long long ex_ml[NCTA * 4];
    unsigned long long ex_pace[NMS * RCNT * 16];
    uint32_t ex_o[NCTA * 256];
    uint32_t ex_part[NCTA * DM * 2];
};
__device__ Scratch g_scratch;

__device__ __forceinline__ uint32_t fu(float x) { return __float_as_uint(x); }
__device__ __forceinline__ float uf(uint32_t x) { return __uint_as_float(x); }
__device__ __forceinline__ uint32_t now_ns() { uint32_t t; asm volatile("mov.u32 %0, %globaltimer_lo;" : "=r"(t)); return t; }
__device__ __forceinline__ void mbar_init(uint32_t b, int c) {
    asm volatile("mbarrier.init.shared::cta.b64 [%0], %1;" ::"r"(b), "r"(c) : "memory");
}
__device__ __forceinline__ void mbar_init_fence() { asm volatile("fence.mbarrier_init.release.cluster;" ::: "memory"); }
__device__ __forceinline__ void mbar_expect(uint32_t b, uint32_t bytes) {
    asm volatile("mbarrier.arrive.expect_tx.shared::cta.b64 _, [%0], %1;" ::"r"(b), "r"(bytes) : "memory");
}
__device__ __forceinline__ void mbar_arrive_if(uint32_t b, uint32_t cnt, bool p) {
    asm volatile("{\n.reg .pred p;\nsetp.ne.u32 p, %2, 0;\n@p mbarrier.arrive.shared::cta.b64 _, [%0], %1;\n}"
                 ::"r"(b), "r"(cnt), "r"((uint32_t)p) : "memory");
}
__device__ __forceinline__ bool mbar_try(uint32_t b) {
    uint32_t ok;
    asm volatile("{\n.reg .pred p;\nmbarrier.try_wait.parity.shared::cta.b64 p, [%1], 0;\nselp.u32 %0, 1, 0, p;\n}"
                 : "=r"(ok) : "r"(b) : "memory");
    return ok;
}
__device__ __forceinline__ bool mbar_test(uint32_t b) {
    uint32_t ok;
    asm volatile("{\n.reg .pred p;\nmbarrier.test_wait.parity.shared::cta.b64 p, [%1], 0;\nselp.u32 %0, 1, 0, p;\n}"
                 : "=r"(ok) : "r"(b) : "memory");
    return ok;
}
__device__ __forceinline__ void mbar_wait(uint32_t b) {
    unsigned n = 0;
    while (!mbar_try(b))
        if (++n > SPIN_LIMIT) __trap();
}
__device__ __forceinline__ void tma3d(uint32_t dst, const CUtensorMap* m, int c0, int c1, uint32_t bar) {
    asm volatile("cp.async.bulk.tensor.3d.shared::cluster.global.mbarrier::complete_tx::bytes [%0], [%1, {%3, %4, %5}], [%2];"
                 ::"r"(dst), "l"(m), "r"(bar), "r"(c0), "r"(c1), "r"(0) : "memory");
}
__device__ __forceinline__ void tma3d_hint(uint32_t dst, const CUtensorMap* m, int c0, int c1, uint32_t bar, uint64_t pol) {
    asm volatile("cp.async.bulk.tensor.3d.shared::cluster.global.mbarrier::complete_tx::bytes.L2::cache_hint [%0], [%1, {%3, %4, %5}], [%2], %6;"
                 ::"r"(dst), "l"(m), "r"(bar), "r"(c0), "r"(c1), "r"(0), "l"(pol) : "memory");
}
__device__ __forceinline__ bool elect_one() {
    uint32_t p;
    asm volatile("{\n.reg .pred p;\nelect.sync _|p, 0xffffffff;\nselp.u32 %0, 1, 0, p;\n}" : "=r"(p));
    return p;
}
__device__ __forceinline__ uint32_t ldg32(const void* p) {
    uint32_t v;
    asm volatile("ld.global.nc.u32 %0, [%1];" : "=r"(v) : "l"(p));
    return v;
}
__device__ __forceinline__ void bar_comp() { asm volatile("bar.sync 1, 288;" ::: "memory"); }
__device__ __forceinline__ void bar_256() { asm volatile("bar.sync 2, 256;" ::: "memory"); }
__device__ __forceinline__ void sts16(uint32_t a, uint32_t v) { asm volatile("st.shared.b16 [%0], %1;" ::"r"(a), "h"((unsigned short)v) : "memory"); }
__device__ __forceinline__ void sts32_if(uint32_t a, uint32_t v, bool p) {
    asm volatile("{\n.reg .pred p;\nsetp.ne.u32 p, %2, 0;\n@p st.shared.b32 [%0], %1;\n}" ::"r"(a), "r"(v), "r"((uint32_t)p) : "memory");
}
__device__ __forceinline__ void sts64_if(uint32_t a, uint32_t v0, uint32_t v1, bool p) {
    asm volatile("{\n.reg .pred p;\nsetp.ne.u32 p, %3, 0;\n@p st.shared.v2.b32 [%0], {%1, %2};\n}" ::"r"(a), "r"(v0), "r"(v1), "r"((uint32_t)p) : "memory");
}
__device__ __forceinline__ void sts128_if(uint32_t a, uint32_t v0, uint32_t v1, uint32_t v2, uint32_t v3, bool p) {
    asm volatile("{\n.reg .pred p;\nsetp.ne.u32 p, %5, 0;\n@p st.shared.v4.b32 [%0], {%1, %2, %3, %4};\n}"
                 ::"r"(a), "r"(v0), "r"(v1), "r"(v2), "r"(v3), "r"((uint32_t)p) : "memory");
}
__device__ __forceinline__ float lds_f(uint32_t a) { float v; asm volatile("ld.shared.f32 %0, [%1];" : "=f"(v) : "r"(a) : "memory"); return v; }
__device__ __forceinline__ float2 lds_f2(uint32_t a) {
    float2 v; asm volatile("ld.shared.v2.f32 {%0,%1}, [%2];" : "=f"(v.x), "=f"(v.y) : "r"(a) : "memory"); return v;
}
__device__ __forceinline__ float4 lds_f4(uint32_t a) {
    float4 v; asm volatile("ld.shared.v4.f32 {%0,%1,%2,%3}, [%4];" : "=f"(v.x), "=f"(v.y), "=f"(v.z), "=f"(v.w) : "r"(a) : "memory"); return v;
}
__device__ __forceinline__ uint4 lds128(uint32_t addr) {
    uint4 v;
    asm volatile("ld.shared.v4.u32 {%0,%1,%2,%3}, [%4];" : "=r"(v.x), "=r"(v.y), "=r"(v.z), "=r"(v.w) : "r"(addr) : "memory");
    return v;
}
__device__ __forceinline__ void ldsm4t(uint32_t (&a)[4], uint32_t addr) {
    asm volatile("ldmatrix.sync.aligned.m8n8.x4.trans.shared.b16 {%0,%1,%2,%3}, [%4];"
                 : "=r"(a[0]), "=r"(a[1]), "=r"(a[2]), "=r"(a[3]) : "r"(addr) : "memory");
}
__device__ __forceinline__ void mma(float (&c)[4], uint32_t a0, uint32_t a1, uint32_t a2, uint32_t a3, uint32_t b0, uint32_t b1) {
    asm volatile("mma.sync.aligned.m16n8k16.row.col.f32.bf16.bf16.f32 {%0,%1,%2,%3}, {%4,%5,%6,%7}, {%8,%9}, {%0,%1,%2,%3};"
                 : "+f"(c[0]), "+f"(c[1]), "+f"(c[2]), "+f"(c[3])
                 : "r"(a0), "r"(a1), "r"(a2), "r"(a3), "r"(b0), "r"(b1));
}
__device__ __forceinline__ void mma(float (&c)[4], const uint32_t (&a)[4], uint32_t b0, uint32_t b1) {
    mma(c, a[0], a[1], a[2], a[3], b0, b1);
}

template <bool ATOM>
__device__ __forceinline__ void rd16(unsigned long long& a, unsigned long long& b, const void* p, uint32_t on) {
    if (ATOM)
        asm volatile("{\n.reg .pred p;\n.reg .b128 z, d;\nsetp.ne.u32 p, %3, 0;\nmov.b128 z, {0, 0};\nmov.b128 d, {%0, %1};\n"
                     "@p atom.relaxed.gpu.global.cas.b128 d, [%2], z, z;\nmov.b128 {%0, %1}, d;\n}"
                     : "+l"(a), "+l"(b) : "l"(p), "r"(on) : "memory");
    else
        asm volatile("{\n.reg .pred p;\nsetp.ne.u32 p, %3, 0;\n@p ld.relaxed.gpu.global.v2.b64 {%0, %1}, [%2];\n}"
                     : "+l"(a), "+l"(b) : "l"(p), "r"(on) : "memory");
}
__device__ __forceinline__ void st_w1(unsigned long long* p, uint32_t v, uint32_t tag, bool on) {
    unsigned long long w = ((unsigned long long)tag << 32) | v;
    asm volatile("{\n.reg .pred p;\nsetp.ne.u32 p, %2, 0;\n@p st.relaxed.gpu.global.b64 [%0], %1;\n}" ::"l"(p), "l"(w), "r"((uint32_t)on) : "memory");
}
__device__ __forceinline__ void st_w2(unsigned long long* p, uint32_t v0, uint32_t v1, uint32_t tag, bool on) {
    unsigned long long w0 = ((unsigned long long)tag << 32) | v0, w1 = ((unsigned long long)tag << 32) | v1;
    asm volatile("{\n.reg .pred p;\nsetp.ne.u32 p, %3, 0;\n@p st.relaxed.gpu.global.v2.b64 [%0], {%1, %2};\n}"
                 ::"l"(p), "l"(w0), "l"(w1), "r"((uint32_t)on) : "memory");
}
template <int N, bool ATOM>
__device__ __forceinline__ void poll2(const unsigned long long* p, const int (&off)[N], uint32_t (&v)[2 * N], uint32_t tag, bool on) {
    unsigned long long w[2 * N];
    uint32_t need[N];
#pragma unroll
    for (int i = 0; i < N; i++) { w[2 * i] = w[2 * i + 1] = (unsigned long long)tag << 32; need[i] = on; }
    unsigned n = 0;
    while (true) {
#pragma unroll
        for (int i = 0; i < N; i++) rd16<ATOM>(w[2 * i], w[2 * i + 1], p + off[i], need[i]);
        uint32_t any = 0;
#pragma unroll
        for (int i = 0; i < N; i++) {
            need[i] = ((uint32_t)(w[2 * i] >> 32) ^ tag) | ((uint32_t)(w[2 * i + 1] >> 32) ^ tag);
            any |= need[i];
        }
        if (!__any_sync(0xffffffffu, any != 0)) break;
        __nanosleep(SLEEP_NS);
        if (++n > SPIN_LIMIT) __trap();
    }
#pragma unroll
    for (int i = 0; i < 2 * N; i++) v[i] = (uint32_t)w[i];
}
__device__ __forceinline__ uint32_t tagf(float v, uint32_t tg) { return (fu(v) & ~3u) | tg; }
__device__ __forceinline__ void st_t1(uint32_t* p, uint32_t v) {
    asm volatile("st.relaxed.gpu.global.b32 [%0], %1;" ::"l"(p), "r"(v) : "memory");
}
__device__ __forceinline__ void st_t4(uint32_t* p, uint32_t a, uint32_t b, uint32_t c, uint32_t d) {
    asm volatile("st.relaxed.gpu.global.v4.b32 [%0], {%1, %2, %3, %4};" ::"l"(p), "r"(a), "r"(b), "r"(c), "r"(d) : "memory");
}
template <int N, int STRIDE, bool ATOM>
__device__ __forceinline__ void poll_lines(const uint32_t* p, float (&v)[N], uint32_t tg) {
    uint32_t w[N];
#pragma unroll
    for (int i = 0; i < N; i++) w[i] = 0;
    unsigned n = 0;
    while (true) {
#pragma unroll
        for (int i = 0; i < N; i++) {
            if (ATOM)
                asm volatile("{\n.reg .pred p;\nsetp.ne.u32 p, %2, 0;\n@p atom.relaxed.gpu.global.or.b32 %0, [%1], 0;\n}"
                             : "+r"(w[i]) : "l"(p + i * STRIDE), "r"((w[i] ^ tg) & 3u) : "memory");
            else
                asm volatile("{\n.reg .pred p;\nsetp.ne.u32 p, %2, 0;\n@p ld.relaxed.gpu.global.b32 %0, [%1];\n}"
                             : "+r"(w[i]) : "l"(p + i * STRIDE), "r"((w[i] ^ tg) & 3u) : "memory");
        }
        uint32_t any = 0;
#pragma unroll
        for (int i = 0; i < N; i++) any |= w[i] ^ tg;
        if (!__any_sync(0xffffffffu, (any & 3u) != 0)) break;
        if (++n > SPIN_LIMIT) __trap();
    }
#pragma unroll
    for (int i = 0; i < N; i++) v[i] = uf(w[i] & ~3u);
}
__device__ __forceinline__ void announce(unsigned int* c, bool on) {
    if (on) asm volatile("red.relaxed.gpu.global.add.u32 [%0], 1;" ::"l"(c) : "memory");
}
template <bool SLEEP>
__device__ __forceinline__ void await_count(const unsigned int* p, unsigned target, uint32_t gate, int lane) {
    unsigned n = 0, c;
    while (true) {
        c = 0;
        if (lane == 0) asm volatile("atom.relaxed.gpu.global.or.b32 %0, [%1], 0;" : "=r"(c) : "l"(p) : "memory");
        c = __shfl_sync(0xffffffffu, c, 0);
        if (c >= target) break;
        if (SLEEP) __nanosleep(SLEEP_NS);
        if (++n > SPIN_LIMIT) __trap();
    }
    mbar_arrive_if(gate, 1, lane == 0);
}

__device__ __forceinline__ float rbf(float x) {
    uint32_t r;
    asm("cvt.rn.bf16x2.f32 %0, %1, 0f00000000;" : "=r"(r) : "f"(x));
    return uf(r);
}
__device__ __forceinline__ uint32_t pack2(float lo, float hi) {
    __nv_bfloat162 v = __floats2bfloat162_rn(lo, hi);
    return *reinterpret_cast<uint32_t*>(&v);
}
__device__ __forceinline__ float bf_lo(uint32_t v) { return uf(v << 16); }
__device__ __forceinline__ float bf_hi(uint32_t v) { return uf(v & 0xffff0000u); }
__device__ __forceinline__ float bf_sel(uint32_t v, int hi) { return hi ? bf_hi(v) : bf_lo(v); }
__device__ __forceinline__ float sel4(int t, float a, float b, float c, float d) {
    return (t & 2) ? ((t & 1) ? d : c) : ((t & 1) ? b : a);
}

__device__ __forceinline__ void ln_part1(const float (&v)[4], uint32_t stats, int warp, int lane) {
    float mean = 0.25f * ((v[0] + v[1]) + (v[2] + v[3]));
    float m2;
    { float a = v[0] - mean, b = v[1] - mean, c = v[2] - mean, d = v[3] - mean; m2 = (a * a + b * b) + (c * c + d * d); }
    float cnt_half = 2.f;
#pragma unroll
    for (int s = 0; s < 4; s++) {
        const int mask = (s == 0) ? 1 : (s == 1) ? 2 : (s == 2) ? 8 : 16;
        const float om = __shfl_xor_sync(0xffffffffu, mean, mask);
        const float o2 = __shfl_xor_sync(0xffffffffu, m2, mask);
        const float d = om - mean;
        m2 = (m2 + o2) + d * d * cnt_half;
        mean = 0.5f * (mean + om);
        cnt_half *= 2.f;
    }
    sts64_if(stats + ((lane >> 2) & 1) * 80 + warp * 8, fu(mean), fu(m2), (lane & ~4) == 0);
}
__device__ __forceinline__ void ln_part2(float (&v)[4], uint32_t stats, int lane) {
    const uint32_t st = stats + ((lane >> 2) & 1) * 80;
    const float4 a = lds_f4(st), b = lds_f4(st + 16), c = lds_f4(st + 32), d = lds_f4(st + 48);
    const float2 e = lds_f2(st + 64);
    const float mu = ((((a.x + a.z) + (b.x + b.z)) + ((c.x + c.z) + (d.x + d.z))) + e.x) * (1.f / 9.f);
    const float M2 = (((a.y + a.w) + (b.y + b.w)) + ((c.y + c.w) + (d.y + d.w))) + e.y;
    const float q0 = a.x - mu, q1 = a.z - mu, q2 = b.x - mu, q3 = b.z - mu, q4 = c.x - mu, q5 = c.z - mu, q6 = d.x - mu,
                q7 = d.z - mu, q8 = e.x - mu;
    const float dd = (((q0 * q0 + q1 * q1) + (q2 * q2 + q3 * q3)) + ((q4 * q4 + q5 * q5) + (q6 * q6 + q7 * q7))) + q8 * q8;
    const float mb = rbf(mu);
    const float vb = rbf((M2 + 64.f * dd) * (1.f / 576.f));
    float sq, rd;
    asm("sqrt.approx.f32 %0, %1;" : "=f"(sq) : "f"(rbf(vb + 1e-5f)));
    asm("rcp.approx.f32 %0, %1;" : "=f"(rd) : "f"(rbf(sq)));
#pragma unroll
    for (int i = 0; i < 4; i++) v[i] = rbf(rbf(v[i] - mb) * rd);
}

__device__ __forceinline__ void spread_b(uint32_t (&b)[4][2], uint32_t r0, uint32_t r1, int lane) {
#pragma unroll
    for (int ks = 0; ks < 4; ks++) {
        const int src = (ks << 3) | (lane & 7);
        b[ks][0] = __shfl_sync(0xffffffffu, r0, src);
        b[ks][1] = __shfl_sync(0xffffffffu, r1, src);
    }
}

__device__ __noinline__ void gemv32(uint32_t tile, uint32_t bar, uint32_t r0, uint32_t r1, uint32_t red, int warp) {
    const int lane = threadIdx.x & 31;
    uint32_t b[4][2];
    spread_b(b, r0, r1, lane);
    float acc[2][4] = {};
    const int rr = (lane & 7) + ((lane >> 4) << 3);
    const uint32_t a0 = tile + (warp * 64 + rr) * 64;
    const int sw = (rr >> 1) & 3, c = (lane >> 3) & 1;
    mbar_wait(bar + 8 * (warp / 3));
#pragma unroll
    for (int ks = 0; ks < 4; ks++) {
#pragma unroll
        for (int mt = 0; mt < 2; mt++) {
            uint32_t a[4];
            ldsm4t(a, a0 + ks * 1024 + (((mt * 2 + c) ^ sw) << 4));
            mma(acc[mt], a, b[ks][0], b[ks][1]);
        }
    }
    const int t = lane & 3, g = lane >> 2;
    sts64_if(red + (warp * 32 + t * 8 + g) * 8, fu(sel4(t, acc[0][0], acc[0][2], acc[1][0], acc[1][2])),
             fu(sel4(t, acc[0][1], acc[0][3], acc[1][1], acc[1][3])), true);
}
__device__ __forceinline__ float2 sum9(uint32_t red) {
    float2 v[9];
#pragma unroll
    for (int w = 0; w < 9; w++) v[w] = lds_f2(red + w * 256);
    return make_float2((((v[0].x + v[1].x) + (v[2].x + v[3].x)) + ((v[4].x + v[5].x) + (v[6].x + v[7].x))) + v[8].x,
                       (((v[0].y + v[1].y) + (v[2].y + v[3].y)) + ((v[4].y + v[5].y) + (v[6].y + v[7].y))) + v[8].y);
}

__device__ __forceinline__ void reduce_part1(const uint32_t* p, uint32_t r2, int warp, int lane, uint32_t tg) {
    float v[16];
    poll_lines<16, DM * 2, false>(p, v, tg);
    const float s = (((v[0] + v[1]) + (v[2] + v[3])) + ((v[4] + v[5]) + (v[6] + v[7]))) +
                    (((v[8] + v[9]) + (v[10] + v[11])) + ((v[12] + v[13]) + (v[14] + v[15])));
    sts32_if(r2 + (warp * 32 + (lane >> 2) + (lane & 2) * 4 + (lane & 1) * 16) * 4, fu(s), true);
}
__device__ __forceinline__ float reduce_part2(uint32_t r2, int lane) {
    float a[8];
#pragma unroll
    for (int w = 0; w < 8; w++) a[w] = lds_f(r2 + (w * 32 + lane) * 4);
    return ((a[0] + a[1]) + (a[2] + a[3])) + ((a[4] + a[5]) + (a[6] + a[7]));
}
__device__ __forceinline__ uint32_t next_epoch(const Scratch* gs) {
    uint32_t e;
    asm volatile("ld.relaxed.gpu.global.u32 %0, [%1];" : "=r"(e) : "l"(&gs->epoch) : "memory");
    return e >= 0x7ffffffeu ? 1u : e + 1;
}

__global__ void __launch_bounds__(NTHR, 1)
fused_block_kernel(const __nv_bfloat16* __restrict__ x, const __nv_bfloat16* __restrict__ cvec, __nv_bfloat16* __restrict__ out,
                   Scratch* __restrict__ gs, const char* __restrict__ kbytes, const __grid_constant__ Params mp)
{
    extern __shared__ __align__(1024) unsigned char smem_raw[];
    const uint32_t base = ((uint32_t)__cvta_generic_to_shared(smem_raw) + 1023u) & ~1023u;
    const uint32_t bars = base + OFF_BAR;
    const bool helper = blockIdx.x < NHELP;
    const int cta = helper ? NCTA + blockIdx.x : blockIdx.x - NHELP;
    const bool heavy = cta >= 96;
    const int mblk0 = helper ? 96 + 3 * blockIdx.x : cta;
    const int krow = ((((cta >> 2) & 1) * 16 + (cta >> 3)) * SK + (SK - WIN)) + (cta & 3) * 64;
    if (!helper && threadIdx.x < 128) asm volatile("prefetch.global.L2 [%0];" ::"l"(kbytes + (size_t)krow * 256 + threadIdx.x * 128));
    uint32_t t_start = now_ns();

    if (threadIdx.x >= 320) {
        const int lane = threadIdx.x & 31, warp = __shfl_sync(0xffffffffu, threadIdx.x >> 5, 0);
        const int nops = helper ? NOPS_HELP : heavy ? NOPS_HEAVY : NOPS_LIGHT;
        uint4 tab0 = make_uint4(0, 0, 0, 0), tab1 = tab0;
        {
            const uint4* ops = mp.op + (helper ? NOPS_LIGHT + NOPS_HEAVY : heavy ? NOPS_LIGHT : 0);
            const int i0 = (warp & 1) + 2 * lane;
            if (i0 < nops) asm volatile("ld.v4.u32 {%0,%1,%2,%3}, [%4];" : "=r"(tab0.x), "=r"(tab0.y), "=r"(tab0.z), "=r"(tab0.w) : "l"(ops + i0));
            if (i0 + 64 < nops) asm volatile("ld.v4.u32 {%0,%1,%2,%3}, [%4];" : "=r"(tab1.x), "=r"(tab1.y), "=r"(tab1.z), "=r"(tab1.w) : "l"(ops + i0 + 64));
        }
        if (warp == 10 && lane >= 1 && lane < M_COUNT) asm volatile("prefetch.tensormap [%0];" ::"l"(&mp.m[lane]) : "memory");
        const int xcol = 4096 + (cta - 96) * 16;
        const int base0 = helper ? (mblk0 + lane - 1) * 32 : lane == 1 ? cta * 32 : lane == 2 ? xcol : 0;
        const int base1 = lane == 1 ? krow : lane == 4 ? cta * 288 : lane == 5 ? xcol * 9 : 0;
        uint64_t pol;
        asm volatile("createpolicy.fractional.L2::evict_first.b64 %0, 1.0;" : "=l"(pol));
        const int cnt = (nops + 1 - (warp & 1)) >> 1;
        bool anchored = false;
        asm volatile("bar.sync 3, 384;" ::: "memory");
#pragma unroll 1
        for (int k = 0; k < cnt; k++) {
            if (k == 32) tab0 = tab1;
            uint4 e;
            e.x = __shfl_sync(0xffffffffu, tab0.x, k); e.y = __shfl_sync(0xffffffffu, tab0.y, k);
            e.z = __shfl_sync(0xffffffffu, tab0.z, k); e.w = __shfl_sync(0xffffffffu, tab0.w, k);
            const uint32_t bar = bars + (e.x >> 24) * 8;
            const int c0 = __shfl_sync(0xffffffffu, base0, (e.x >> 10) & 3);
            const int c1 = (e.y & 0xfff) + __shfl_sync(0xffffffffu, base1, (e.x >> 12) & 7);
            const uint32_t dst = base + (e.x & 0x3ff) * 256;
            const CUtensorMap* map = &mp.m[(e.x >> 15) & 15];
            mbar_wait(bars + ((e.y >> 12) & 0xff) * 8);
            if (lane == 0) mbar_expect(bar, ((e.x >> 19) & 15) << 10);
            if (!anchored) t_start = fu(lds_f(base + OFF_T0));
            if (e.x & (1u << 23)) {
                const int lag = (int)(now_ns() - (t_start + (e.y >> 20) * 16)) + ANCHOR_BIAS;
                if (lag > 0) t_start += lag;
                anchored = true;
            }
            const uint32_t due = t_start + (e.y >> 20) * 16;
            unsigned n = 0;
            while (true) {
                const int lvl = min(max(PACE_MID + ((int)(now_ns() - due) >> PACE_SHIFT), 0), 7);
                if (mbar_test(bars + (__byte_perm(e.z, e.w, lvl) & 0xff) * 8)) break;
                if (++n > 64 * SPIN_LIMIT) __trap();
            }
            if (lane == 0) tma3d_hint(dst, map, c0, c1, bar, pol);
            __syncwarp();
        }
        return;
    }

    if (threadIdx.x == 32 && !helper) {
#pragma unroll
        for (int i = 0; i < K_AT_START; i++) mbar_init(bars + 8 * (U_KV + i), 1);
        mbar_init_fence();
#pragma unroll
        for (int i = 0; i < K_AT_START; i++) {
            mbar_expect(bars + 8 * (U_KV + i), CH);
            asm volatile("cp.async.bulk.shared::cluster.global.mbarrier::complete_tx::bytes [%0], [%1], %2, [%3];"
                         ::"r"(base + (S0 + i) * CH), "l"(kbytes + (size_t)krow * 256 + i * CH), "r"(CH), "r"(bars + 8 * (U_KV + i)) : "memory");
        }
    }
    if (threadIdx.x == 0) {
        const bool q1 = heavy && !helper;
        const uint32_t bb = bars + (q1 ? 8 * U_WQ : 0), dst = base + (q1 ? OFF_WQ : OFF_WMOD);
#pragma unroll
        for (int i = 0; i < 3; i++) { mbar_init(bars + 8 * i, 1); mbar_init(bars + 8 * (U_WQ + i), 1); }
        mbar_init_fence();
#pragma unroll
        for (int i = 0; i < 3; i++) {
            mbar_expect(bb + 8 * i, 12288);
            tma3d(dst + i * 12288, &mp.m[q1 ? M_WQ : M_WMOD], mblk0 * 32, i * 192, bb + 8 * i);
        }
    }
    int tid;
    asm volatile("mov.u32 %0, %tid.x;" : "=r"(tid));
    const int lane = tid & 31;
    const int warp = __shfl_sync(0xffffffffu, tid >> 5, 0);
    if (elect_one()) {
        if (warp < 7) {
            const uint32_t b0 = bars + warp * 128;
            if (warp != 0 && warp != 5) {
#pragma unroll
                for (int i = 0; i < 3; i++) mbar_init(b0 + 8 * i, 1);
            }
            if (warp != 6) {
#pragma unroll
                for (int i = 6; i < 16; i++) mbar_init(b0 + 8 * i, 1);
            }
#pragma unroll
            for (int i = 3; i < 6; i++)
                if (i >= 3 + K_AT_START || warp != 0 || helper) mbar_init(b0 + 8 * i, 1);
            mbar_arrive_if(bars + 8 * B_DONE, 1, warp == 5);
        }
        if (warp >= 6) {
#pragma unroll
            for (int i = 0; i < 16; i++) mbar_init(bars + 8 * (B_USED + (warp - 6) * 16 + i), 8);
        }
        mbar_init_fence();
    }
    sts32_if(base + OFF_T0, t_start, tid == 64);
    __syncwarp();
    asm volatile("bar.arrive 3, 384;\nbar.sync 8, 320;" ::: "memory");

    if (warp == 9) {
        if (helper) return;
        const uint32_t ep = next_epoch(gs);
        unsigned int (*cnt)[RCNT][32] = gs->cnt[ep % 3];
        if (cta < C_COUNT && lane < RCNT) st_t1(&gs->cnt[(ep + 1) % 3][cta][lane][0], 0u);
        await_count<true>(cnt[C_MOD][cta % RCNT], HINT_MOD, bars + 8 * B_GATE_MOD, lane);
#pragma unroll 1
        for (int k = 0; k < NMS; k++) {
            mbar_wait(bars + 8 * (U_KV + MS_FIRST + k * MS_STEP));
            const uint32_t tl = now_ns();
            unsigned old = 0;
            if (lane == 0 && !heavy) asm volatile("atom.relaxed.gpu.global.add.u32 %0, [%1], 1;" : "=r"(old) : "l"(cnt[C_PACE][k]) : "memory");
            old = __shfl_sync(0xffffffffu, old, 0);
            st_w1(gs->ex_pace + (k * RCNT + (lane & (RCNT - 1))) * 16, tl, ep, old == MS_RANK && lane < RCNT);
            mbar_wait(bars + 8 * (U_KV + MS_FIRST + k * MS_STEP + MS_DELAY));
            unsigned long long w = 0;
            if (lane == 0) asm volatile("atom.relaxed.gpu.global.or.b64 %0, [%1], 0;" : "=l"(w) : "l"(gs->ex_pace + (k * RCNT + cta % RCNT) * 16) : "memory");
            sts32_if(base + OFF_T0, (uint32_t)w - mp.nom[k], lane == 0 && (uint32_t)(w >> 32) == ep);
            __syncwarp();
        }
        mbar_wait(bars + 8 * (U_KV + 63));
        {
            float v[8];
            poll_lines<8, 256, true>(gs->ex_o + (cta & ~7) * 256 + (cta & 7) * 32 + lane, v, 1 + ep % 3);
            const float o0 = (v[0] + v[1]) + (v[2] + v[3]), o1 = (v[4] + v[5]) + (v[6] + v[7]);
            const float r = __shfl_xor_sync(0xffffffffu, (lane & 1) ? o0 : o1, 1);
            const int wi = lane >> 1;
            sts32_if(base + OFF_OB + ((lane & 1) * 16 + (wi & 3) * 4 + (wi >> 2)) * 4, (lane & 1) ? pack2(r, o1) : pack2(o0, r), true);
        }
        asm volatile("bar.arrive 4, 320;" ::: "memory");
#pragma unroll 1
        for (int k = cta < NRED ? C_AO : C_X1; k <= C_X1; k++)
            await_count<false>(cnt[k][cta % (k ? RCNT : RCNT0)], k ? HINT_X1 : HINT_AO, bars + 8 * (B_GATE_AO + k), lane);
        asm volatile("bar.sync 6, 320;" ::: "memory");
#pragma unroll
        for (int h = 0; h < 2; h++) {
            if (h == 0 || heavy) {
                const int ci = h * 32 + (h ? lane & 15 : lane);
                float4 u[9];
#pragma unroll
                for (int w = 0; w < 9; w++) u[w] = lds_f4(base + OFF_SC + (w * 48 + ci) * 16);
                float4 s;
                s.x = (((u[0].x + u[1].x) + (u[2].x + u[3].x)) + ((u[4].x + u[5].x) + (u[6].x + u[7].x))) + u[8].x;
                s.y = (((u[0].y + u[1].y) + (u[2].y + u[3].y)) + ((u[4].y + u[5].y) + (u[6].y + u[7].y))) + u[8].y;
                s.z = (((u[0].z + u[1].z) + (u[2].z + u[3].z)) + ((u[4].z + u[5].z) + (u[6].z + u[7].z))) + u[8].z;
                s.w = (((u[0].w + u[1].w) + (u[2].w + u[3].w)) + ((u[4].w + u[5].w) + (u[6].w + u[7].w))) + u[8].w;
                float g0 = rbf(s.x), g1 = rbf(s.y);
                g0 = g0 * (g0 > 0.f ? 1.f : 0.f);
                g1 = g1 * (g1 > 0.f ? 1.f : 0.f);
                const uint32_t hp = pack2(g0 * rbf(s.z), g1 * rbf(s.w));
                sts16(base + OFF_HH + ci * 2, hp);
                sts16(base + OFF_HH + 128 + ci * 2, hp >> 16);
            }
        }
        asm volatile("bar.arrive 7, 320;" ::: "memory");
        return;
    }

    const int kvh = cta >> 3, bat = (cta >> 2) & 1;
    const int nmod = helper ? 3 : heavy ? 0 : 1;
    const int g = lane >> 2, t = lane & 3;
    const int fb = g & 1;
    const int col0 = warp * 64 + (g >> 1) * 16 + 2 * t;
    const bool reducer = cta < NRED;
    const int rcol = (reducer ? cta : 0) * 16 + (lane & 15), rb_ = lane >> 4;
    const uint32_t s_sc = base + OFF_SC, s_stats = base + OFF_ST, s_r2 = base + OFF_R2;
    const uint32_t ca_ = ldg32(cvec + fb * DM + col0), cb_ = ldg32(cvec + fb * DM + col0 + 8);
    const uint32_t xa = ldg32(x + fb * DM + col0), xb = ldg32(x + fb * DM + col0 + 8);
    const uint32_t tag = next_epoch(gs);
    const float xr = bf_sel(ldg32(x + rb_ * DM + (rcol & ~1)), lane & 1);
    unsigned int (*cnt)[RCNT][32] = gs->cnt[tag % 3];

    float y[4] = {bf_lo(xa), bf_hi(xa), bf_lo(xb), bf_hi(xb)};
    {
        float cv[4] = {bf_lo(ca_), bf_hi(ca_), bf_lo(cb_), bf_hi(cb_)};
#pragma unroll
        for (int i = 0; i < 4; i++) cv[i] = cv[i] / (1.f + expf(-cv[i]));
        const uint32_t s01 = pack2(cv[0], cv[1]), s23 = pack2(cv[2], cv[3]);
        ln_part1(y, s_stats, warp, lane);
#pragma unroll 1
        for (int m = 0; m < nmod; m++)
            gemv32(base + OFF_WMOD + m * 36864, bars + 8 * (m == 1 ? U_WQ : m == 2 ? 3 : 0), s01, s23, s_sc + m * 2304, warp);
    }
    bar_comp();
    if (warp < nmod) {
        const float2 s2 = sum9(s_sc + warp * 2304 + lane * 8);
#pragma unroll
        for (int r = 0; r < REP1; r++) st_w1(gs->ex_mod + r * 6 * DM + (mblk0 + warp) * 32 + lane, pack2(s2.x, s2.y), tag, true);
        announce(cnt[C_MOD][lane & (RCNT - 1)], cta < 36 && lane < RCNT);
    }
    if (helper) return;
    mbar_arrive_if(bars + 8 * B_MODFREE, 1, tid == 256);
    ln_part2(y, s_stats, lane);
    const int rr = (lane & 7) + ((lane >> 4) << 3), hi8 = (lane >> 3) & 1;
    float cbv[4], sbv[4], gar, gbr;
    const int zoff[1] = {0};
    {
        const unsigned long long* mod = gs->ex_mod + (cta % REP1) * 6 * DM;
        const int moff[4] = {0, 8, DM, DM + 8};
        uint32_t v[8];
        mbar_wait(bars + 8 * B_GATE_MOD);
        poll2<4, false>(mod + col0, moff, v, tag, true);
        float h[4];
#pragma unroll
        for (int i = 0; i < 4; i++) h[i] = rbf(y[i] * rbf(1.f + bf_sel(v[4 + i], fb))) + bf_sel(v[i], fb);
        gemv32(base + OFF_WQ, bars + 8 * U_WQ, pack2(h[0], h[1]), pack2(h[2], h[3]), s_sc + 2304, warp);
        bar_comp();
        if (warp == 0) {
            const float2 s2 = sum9(s_sc + 2304 + lane * 8);
            const float o0 = __shfl_xor_sync(0xffffffffu, s2.x, 1), o1 = __shfl_xor_sync(0xffffffffu, s2.y, 1);
            st_w1(gs->ex_q + (lane & 1) * 2048 + cta * 16 + (lane >> 1), (lane & 1) ? pack2(o1, s2.y) : pack2(s2.x, o0), tag, true);
        }
        mbar_arrive_if(bars + 8 * B_WQFREE, 1, tid == 256);
        poll2<4, false>(mod + 3 * DM + col0, moff, v, tag, true);
#pragma unroll
        for (int i = 0; i < 4; i++) { sbv[i] = bf_sel(v[i], fb); cbv[i] = rbf(1.f + bf_sel(v[4 + i], fb)); }
        if (warp < 2) {
            uint32_t qv[2];
            poll2<1, true>(gs->ex_q + bat * 2048 + kvh * 128 + tid * 2, zoff, qv, tag, true);
            sts64_if(base + OFF_Q + tid * 8, qv[0], qv[1], true);
        }
        bar_comp();
        const int goff[2] = {0, 3 * DM};
        uint32_t gv[4];
        poll2<2, false>(mod + 2 * DM + (rcol & ~1), goff, gv, tag, reducer && warp == RED_WARP);
        gar = bf_sel((lane & 1) ? gv[1] : gv[0], rb_);
        gbr = bf_sel((lane & 1) ? gv[3] : gv[2], rb_);
    }

    const int line0 = rr * 9 + warp;
    const uint32_t rowa = base + line0 * 128;
    const uint32_t lsw = line0 & 7;
    uint32_t wf[4][4][4];
    const uint32_t tg0 = 1 + tag % 3, tg1 = 1 + (2 * (tag % 3)) % 3, tg2 = 1 + (2 * (tag % 3) + 1) % 3;
    unsigned long long* x1dst = gs->ex_x1 + ((lane >> 3) & 1) * 288 + cta * 8 + rb_ * 4 + ((lane >> 1) & 3);
    uint32_t* part = gs->ex_part + cta * (DM * 2) + (warp * 4 + t) * 32 + g * 4;
    const bool x1pub = reducer && warp == RED_WARP && (lane & 1) == 0;
    auto prewrite = [&]() { st_t4(part, 0u, 0u, 0u, 0u); st_w1(x1dst, 0u, 0u, x1pub); };
    auto publish = [&](const float (&acc)[4][4], uint32_t tg) {
        st_t4(part, tagf(sel4(t, acc[0][0], acc[1][0], acc[2][0], acc[3][0]), tg), tagf(sel4(t, acc[0][1], acc[1][1], acc[2][1], acc[3][1]), tg),
              tagf(sel4(t, acc[0][2], acc[1][2], acc[2][2], acc[3][2]), tg), tagf(sel4(t, acc[0][3], acc[1][3], acc[2][3], acc[3][3]), tg));
    };

    if (warp < 8) {
        uint4 qf[4];
#pragma unroll
        for (int j = 0; j < 4; j++) qf[j] = lds128(base + OFF_Q + (g & 1) * 256 + ((j ^ ((g >> 1) & 1)) << 6) + t * 16);
        float mx0 = -INFINITY, mx1 = -INFINITY;
        const uint32_t rowoff = base + ((warp & 1) * 16 + g) * 256 + t * 16;
        const uint32_t sw = (g & 1) << 6;
        const bool valid = (g & 1) == (t & 1);
        uint32_t scp = s_sc + (warp * 16 + g + ((t & 2) << 2)) * 4;
#pragma unroll 1
        for (int c = warp >> 1; c < 32; c += 4) {
            const int s = c + S0 >= NS ? c + S0 - NS : c + S0;
            mbar_wait(bars + 8 * (U_KV + c));
            const uint32_t a0 = rowoff + s * CH;
            float acc[4] = {}, acc2[4] = {};
#pragma unroll
            for (int j = 0; j < 4; j++) {
                const uint32_t o = (j << 6) ^ sw;
                const uint4 lo = lds128(a0 + o), hi = lds128(a0 + 2048 + o);
                mma(acc, lo.x, hi.x, lo.y, hi.y, qf[j].x, qf[j].y);
                mma(acc2, lo.z, hi.z, lo.w, hi.w, qf[j].z, qf[j].w);
            }
            __syncwarp();
            mbar_arrive_if(bars + 8 * (B_USED + c), 4, lane == 0);
            float u0 = (t & 2) ? acc[2] + acc2[2] : acc[0] + acc2[0];
            float u1 = (t & 2) ? acc[3] + acc2[3] : acc[1] + acc2[1];
            u0 = rbf(rbf(u0) * 0.08838834764831845f);
            u1 = rbf(rbf(u1) * 0.08838834764831845f);
            sts32_if(scp, fu(u0), valid);
            sts32_if(scp + 4096, fu(u1), valid);
            mx0 = valid ? fmaxf(mx0, u0) : mx0;
            mx1 = valid ? fmaxf(mx1, u1) : mx1;
            scp += 512;
        }
#pragma unroll
        for (int m = 1; m < 32; m <<= 1) {
            mx0 = fmaxf(mx0, __shfl_xor_sync(0xffffffffu, mx0, m));
            mx1 = fmaxf(mx1, __shfl_xor_sync(0xffffffffu, mx1, m));
        }
        sts64_if(s_stats + warp * 8, fu(mx0), fu(mx1), lane == 0);
        bar_256();
        const int uh = g & 1;
        float mloc = -INFINITY;
#pragma unroll
        for (int w = 0; w < 8; w++) mloc = fmaxf(mloc, lds_f(s_stats + (2 * w + uh) * 4));
        float e[8];
#pragma unroll
        for (int i = 0; i < 4; i++) {
            const float2 v = lds_f2(s_sc + (uh * 1024 + (tid >> 3) * 32 + 2 * t + i * 8) * 4);
            e[2 * i] = __expf(v.x - mloc);
            e[2 * i + 1] = __expf(v.y - mloc);
        }
        float l = ((e[0] + e[1]) + (e[2] + e[3])) + ((e[4] + e[5]) + (e[6] + e[7]));
        l += __shfl_xor_sync(0xffffffffu, l, 1);
        l += __shfl_xor_sync(0xffffffffu, l, 2);
        l += __shfl_xor_sync(0xffffffffu, l, 8);
        l += __shfl_xor_sync(0xffffffffu, l, 16);
        sts32_if(s_stats + (16 + 2 * warp + uh) * 4, fu(l), (lane & ~4) == 0);
        bar_256();
        if (warp == 0) {
            float lt = 0.f;
#pragma unroll
            for (int w = 0; w < 8; w++) lt += lds_f(s_stats + (16 + 2 * w + uh) * 4);
            st_w2(gs->ex_ml + cta * 4 + uh * 2, fu(mloc), fu(lt), tag, (lane & ~4) == 0);
            uint32_t ml[2];
            poll2<1, true>(gs->ex_ml + ((cta & ~3) + t) * 4 + uh * 2, zoff, ml, tag, true);
            const float ms = uf(ml[0]), ls = uf(ml[1]);
            float M = fmaxf(ms, __shfl_xor_sync(0xffffffffu, ms, 1));
            M = fmaxf(M, __shfl_xor_sync(0xffffffffu, M, 2));
            float L = ls * __expf(ms - M);
            L += __shfl_xor_sync(0xffffffffu, L, 1);
            L += __shfl_xor_sync(0xffffffffu, L, 2);
            sts32_if(s_stats + (32 + uh) * 4, fu(__expf(mloc - M) / L), (lane & ~4) == 0);
        }
        bar_256();
        const float f = lds_f(s_stats + (32 + uh) * 4);
        sts128_if(base + OFF_P + tid * 16, pack2(e[0] * f, e[1] * f), pack2(e[2] * f, e[3] * f), pack2(e[4] * f, e[5] * f),
                  pack2(e[6] * f, e[7] * f), true);
        bar_256();

        float acc[4] = {}, acc2[4] = {};
        const int cc = (warp & 3) * 2 + hi8;
        const uint32_t voff = base + (warp >> 2) * (CH / 2) + rr * 128 + ((cc ^ (lane & 7)) << 4);
        uint32_t poff = base + OFF_P + (g & 1) * 64 + t * 16;
        uint32_t* odst = gs->ex_o + cta * 256 + (t & 1) * 128 + warp * 16 + ((t & 2) << 2) + g;
#pragma unroll 1
        for (int c = 32; c < 64; c++) {
            const int s = c + S0 >= 2 * NS ? c + S0 - 2 * NS : c + S0 - NS;
            if (c == PREWRITE_AT) { st_t1(odst, 0u); prewrite(); }
            const uint4 p0 = lds128(poff);
            poff += 128;
            mbar_wait(bars + 8 * (U_KV + c));
            uint32_t a[4], a2[4];
            ldsm4t(a, voff + s * CH);
            ldsm4t(a2, voff + s * CH + 2048);
            mma(acc, a, p0.x, p0.y);
            mma(acc2, a2, p0.z, p0.w);
            __syncwarp();
            mbar_arrive_if(bars + 8 * (B_USED + c), 1, lane == 0);
        }
        st_t1(odst, tagf(sel4(t, acc[0] + acc2[0], acc[1] + acc2[1], acc[2] + acc2[2], acc[3] + acc2[3]), tg0));
    } else {
        mbar_wait(bars + 8 * (U_KV + PREWRITE_AT));
        prewrite();
    }
    {
#pragma unroll
        for (int ks = 0; ks < 2; ks++) {
            mbar_wait(bars + 8 * (U_WO + 2 * ks)); mbar_wait(bars + 8 * (U_WO + 2 * ks + 1));
#pragma unroll
            for (int mt = 0; mt < 4; mt++) ldsm4t(wf[ks][mt], rowa + OFF_WO + ks * 18432 + (((mt * 2 + hi8) ^ lsw) << 4));
        }
        asm volatile("bar.sync 4, 320;" ::: "memory");
        const uint4 ob = lds128(base + OFF_OB + fb * 64 + t * 16);
        float acc[4][4] = {};
#pragma unroll
        for (int mt = 0; mt < 4; mt++) mma(acc[mt], wf[0][mt], ob.x, ob.y);
#pragma unroll
        for (int mt = 0; mt < 4; mt++) mma(acc[mt], wf[1][mt], ob.z, ob.w);
        publish(acc, tg1);
        announce(cnt[C_AO][lane & (RCNT - 1)], warp == 8 && lane < RCNT0);
    }
    const uint32_t gub = bars + 8 * (U_GU + 2 * (warp / 3));
    const uint32_t gxb = heavy ? bars + 8 * (U_GX + 2 * (warp / 3)) : gub;
    uint32_t dn[3][4][4];
    auto load_gu = [&]() {
        const uint32_t rb = base + OFF_GU + hi8 * 36864 + (warp * 64 + rr) * 64;
#pragma unroll
        for (int ks = 0; ks < 4; ks++)
#pragma unroll
            for (int j = 0; j < 4; j++) ldsm4t(wf[ks][j], rb + ks * 1024 + ((j ^ ((rr >> 1) & 3)) << 4));
        if (heavy) {
            const uint32_t rx = base + OFF_GX + hi8 * 18432 + (warp * 64 + rr) * 32;
#pragma unroll
            for (int ks = 0; ks < 4; ks++)
#pragma unroll
                for (int j = 0; j < 2; j++) ldsm4t(dn[1 + j][ks], rx + ks * 512 + ((j ^ ((rr >> 2) & 1)) << 4));
        }
    };
    auto load_dn = [&](int ks) {
#pragma unroll
        for (int mt = 0; mt < 4; mt++) ldsm4t(dn[ks][mt], rowa + OFF_DN + ks * 18432 + (((mt * 2 + hi8) ^ lsw) << 4));
    };
    auto dn_in = [&](int ks) {
        return __all_sync(0xffffffffu, mbar_test(bars + 8 * (U_DN + 2 * ks)) && mbar_test(bars + 8 * (U_DN + 2 * ks + 1)));
    };
    bool have_gu = false, have_dn = false;
    auto try_gu = [&]() {
        if (!have_gu && __all_sync(0xffffffffu, mbar_test(gxb + 8) && mbar_test(gxb) && mbar_test(gub + 8) && mbar_test(gub))) {
            load_gu();
            have_gu = true;
        }
    };
    auto gate = [&](uint32_t gb) {
        unsigned n = 0;
        while (true) {
            try_gu();
            if (__all_sync(0xffffffffu, have_gu ? mbar_try(gb) : mbar_test(gb))) break;
            if (++n > 64 * SPIN_LIMIT) __trap();
        }
    };
    const uint32_t* rsrc = gs->ex_part + (warp & 7) * 16 * (DM * 2) + cta * 32 + lane;
    float x1r = 0.f;
    if (reducer) {
        gate(bars + 8 * B_GATE_AO);
        if (warp < 8) reduce_part1(rsrc, s_r2, warp, lane, tg1);
        bar_comp();
        if (warp == RED_WARP) {
            x1r = rbf(xr + rbf(gar * rbf(reduce_part2(s_r2, lane))));
            const float other = __shfl_xor_sync(0xffffffffu, x1r, 1);
            st_w1(x1dst, pack2(x1r, other), tag, x1pub);
            announce(cnt[C_X1][lane & (RCNT - 1)], lane < RCNT);
        }
    }
    gate(bars + 8 * B_GATE_X1);
    {
        unsigned long long w0, w1;
        unsigned n = 0;
        while (true) {
            asm volatile("ld.relaxed.gpu.global.b64 %0, [%1];" : "=l"(w0) : "l"(gs->ex_x1 + tid) : "memory");
            asm volatile("ld.relaxed.gpu.global.b64 %0, [%1];" : "=l"(w1) : "l"(gs->ex_x1 + 288 + tid) : "memory");
            try_gu();
            if (!have_dn && dn_in(0)) { load_dn(0); have_dn = true; }
            if (__all_sync(0xffffffffu, (uint32_t)(w0 >> 32) == tag && (uint32_t)(w1 >> 32) == tag)) break;
            if (++n > SPIN_LIMIT) __trap();
        }
        y[0] = bf_lo((uint32_t)w0); y[1] = bf_hi((uint32_t)w0); y[2] = bf_lo((uint32_t)w1); y[3] = bf_hi((uint32_t)w1);
        ln_part1(y, s_stats, warp, lane);
        if (!have_gu) { mbar_wait(gub); mbar_wait(gub + 8); mbar_wait(gxb); mbar_wait(gxb + 8); load_gu(); }
        bar_comp();
        ln_part2(y, s_stats, lane);
        uint32_t bfr[4][2];
        spread_b(bfr, pack2(rbf(y[0] * cbv[0]) + sbv[0], rbf(y[1] * cbv[1]) + sbv[1]),
                 pack2(rbf(y[2] * cbv[2]) + sbv[2], rbf(y[3] * cbv[3]) + sbv[3]), lane);
        const uint32_t red = s_sc + (warp * 48 + g + t * 8) * 16;
        float acc[4][4] = {};
#pragma unroll
        for (int ks = 0; ks < 4; ks++)
#pragma unroll
            for (int j = 0; j < 4; j++) mma(acc[j], wf[ks][j], bfr[ks][0], bfr[ks][1]);
        if (heavy) {
            float ax[2][4] = {};
#pragma unroll
            for (int ks = 0; ks < 4; ks++)
#pragma unroll
                for (int j = 0; j < 2; j++) mma(ax[j], dn[1 + j][ks], bfr[ks][0], bfr[ks][1]);
            sts128_if(red + 512, fu(t ? ax[1][0] : ax[0][0]), fu(t ? ax[1][1] : ax[0][1]), fu(t ? ax[1][2] : ax[0][2]),
                      fu(t ? ax[1][3] : ax[0][3]), t < 2);
        }
        sts128_if(red, fu(sel4(t, acc[0][0], acc[1][0], acc[2][0], acc[3][0])), fu(sel4(t, acc[0][1], acc[1][1], acc[2][1], acc[3][1])),
                  fu(sel4(t, acc[0][2], acc[1][2], acc[2][2], acc[3][2])), fu(sel4(t, acc[0][3], acc[1][3], acc[2][3], acc[3][3])), true);
        asm volatile("bar.arrive 6, 320;" ::: "memory");
    }
    {
        bool got[3];
#pragma unroll
        for (int ks = 0; ks < 3; ks++) {
            got[ks] = ks == 0 && have_dn;
            if (!got[ks] && (ks < 2 || heavy) && dn_in(ks)) { load_dn(ks); got[ks] = true; }
        }
        asm volatile("bar.sync 7, 320;" ::: "memory");
        uint32_t hb[6];
#pragma unroll
        for (int i = 0; i < 6; i++) hb[i] = fu(lds_f(base + OFF_HH + (fb * 32 + t + i * 4) * 4));
        float acc[4][4] = {};
#pragma unroll
        for (int ks = 0; ks < 3; ks++) {
            if (ks < 2 || heavy) {
                if (!got[ks]) {
                    mbar_wait(bars + 8 * (U_DN + 2 * ks)); mbar_wait(bars + 8 * (U_DN + 2 * ks + 1));
                    load_dn(ks);
                }
#pragma unroll
                for (int mt = 0; mt < 4; mt++) mma(acc[mt], dn[ks][mt], hb[2 * ks], hb[2 * ks + 1]);
            }
        }
        publish(acc, tg2);
    }
    if (reducer) {
        if (warp < 8) reduce_part1(rsrc, s_r2, warp, lane, tg2);
        bar_comp();
        if (warp == RED_WARP) {
            const float r = x1r + rbf(gbr * rbf(reduce_part2(s_r2, lane)));
            const float other = __shfl_xor_sync(0xffffffffu, r, 1);
            if (x1pub) *reinterpret_cast<uint32_t*>(out + rb_ * DM + rcol) = pack2(r, other);
            if (cta == 0 && lane == 0) st_t1(&gs->epoch, tag);
        }
    }
}

typedef CUresult (*EncodeFn)(CUtensorMap*, CUtensorMapDataType, cuuint32_t, void*, const cuuint64_t*, const cuuint64_t*,
                             const cuuint32_t*, const cuuint32_t*, CUtensorMapInterleave, CUtensorMapSwizzle,
                             CUtensorMapL2promotion, CUtensorMapFloatOOBfill);

void make_map(EncodeFn enc, CUtensorMap* m, const void* p, uint64_t cols, uint64_t rows, uint32_t bc, uint32_t br,
              CUtensorMapSwizzle sw, CUtensorMapL2promotion prom, bool split_halves = false) {
    cuuint64_t gd[3] = {split_halves ? cols / 2 : cols, rows, split_halves ? 2u : 1u};
    cuuint64_t gs[2] = {cols * 2, split_halves ? cols : cols * 2 * rows};
    cuuint32_t bx[3] = {bc, br, split_halves ? 2u : 1u};
    cuuint32_t es[3] = {1, 1, 1};
    enc(m, CU_TENSOR_MAP_DATA_TYPE_BFLOAT16, 3, const_cast<void*>(p), gd, gs, bx, es, CU_TENSOR_MAP_INTERLEAVE_NONE, sw, prom,
        CU_TENSOR_MAP_FLOAT_OOB_FILL_NONE);
}

void build_ops(uint4* list, bool heavy, int* nom) {
    constexpr int NMAX = NOPS_HEAVY + NPRE;
    uint4 op[NMAX];
    int order[NMAX], n = 0;
    for (int u = 0; u < 3; u++) order[n++] = heavy ? U_WQ + u : u;
    for (int u = U_KV; u < U_KV + K_AT_START; u++) order[n++] = u;
    if (!heavy) for (int u = 0; u < 3; u++) order[n++] = U_WQ + u;
    for (int u = U_KV + K_AT_START; u < U_WO; u++) order[n++] = u;
    const int n_v = n;
    for (int k = 0; k < 4; k++) order[n++] = U_WO + k;
    for (int k = 0; k < 3; k++) {
        order[n++] = U_GU + 2 * k; order[n++] = U_GU + 2 * k + 1;
        if (heavy) { order[n++] = U_GX + 2 * k; order[n++] = U_GX + 2 * k + 1; }
    }
    for (int k = 0; k < (heavy ? 6 : 4); k++) order[n++] = U_DN + k;
    int kb[NMAX], win[NMAX], cum[NMAX + 1];
    cum[0] = 0;
    for (int i = 0; i < n; i++) {
        const int u = order[i];
        int dst, sel0 = 0, sel1 = 0, row = 0, map, spb = -1;
        win[i] = WIN_TAIL;
        if (u < U_KV || (u >= U_WQ && u < U_GX)) {
            const int k = u < U_KV ? u : u - U_WQ + 3;
            map = k < 3 ? M_WMOD : M_WQ; dst = OFF_WMOD + k * 12288; sel0 = 1; row = (k % 3) * 192; kb[i] = 12;
            spb = B_DONE; win[i] = WIN_MID;
        } else if (u < U_WO) {
            const int c = u - U_KV, slot = (c + S0) % NS;
            map = c < 32 ? M_K : M_V; dst = slot * CH; sel1 = 1; row = ((c & 31) >> 1) * 256 + (c & 1) * 32; kb[i] = 8;
            spb = c >= NS ? B_USED + c - NS : (slot >= 9 && slot <= 13) ? B_WQFREE : (slot >= 5 && slot < 9) ? B_MODFREE : B_DONE;
            win[i] = c < 64 - END_CHUNKS ? WIN_MID : WIN_END;
        } else if (u < U_GU) {
            const int k = u - U_WO;
            map = M_WO; dst = OFF_WO + k * 9216; sel1 = 4; row = k * 72; kb[i] = 9; win[i] = WIN_END;
        } else if (u < U_WQ) {
            const int k = u - U_GU;
            map = M_GATE + (k & 1); dst = OFF_GU + (k & 1) * 36864 + (k >> 1) * 12288; sel0 = 1; row = (k >> 1) * 192; kb[i] = 12;
        } else if (u < U_DN) {
            const int k = u - U_GX;
            map = M_GATEX + (k & 1); dst = OFF_GX + (k & 1) * 18432 + (k >> 1) * 6144; sel0 = 2; row = (k >> 1) * 192; kb[i] = 6;
        } else {
            const int k = u - U_DN;
            map = M_DN; dst = OFF_DN + k * 9216; kb[i] = 9; win[i] = WIN_LAST;
            if (k < 4) { sel1 = 4; row = k * 72; } else { sel1 = 5; row = (k - 4) * 72; }
        }
        if (heavy && i >= n_v) win[i] += WIN_HEAVY_EXTRA;
        if (spb < 0) spb = B_USED + 64 - NS + ((dst + kb[i] * 1024 - 1) >> 13);
        cum[i + 1] = cum[i] + kb[i];
        op[i].x = (dst >> 8) | (sel0 << 10) | (sel1 << 12) | (map << 15) | (kb[i] << 19) | ((unsigned)u << 24) |
                  ((i == n_v - ANCHOR_BACK || i == n_v - ANCHOR_BACK + 1) ? 1u << 23 : 0u);
        op[i].y = row | (spb << 12);
    }
    const double tv = heavy ? PACE_TV_HEAVY : PACE_TV;
    for (int i = 0; i < n; i++) {
        double due = i <= n_v ? PACE_T0 + (tv - PACE_T0) * cum[i] / cum[n_v] : tv + (PACE_TE - tv) * (cum[i] - cum[n_v]) / (cum[n] - cum[n_v]);
        if (due < 0) due = 0;
        op[i].y |= (unsigned)(due / 16) << 20;
        for (int k = 0; k < NMS; k++)
            if (nom && order[i] == U_KV + MS_FIRST + k * MS_STEP + 5) nom[k] = (int)due;
        unsigned long long lv = 0;
        for (int l = 0; l < 8; l++) {
            int w = win[i] + (l - PACE_MID) * PACE_STEP, wd = B_DONE;
            if (w < PACE_WMIN) w = PACE_WMIN;
            if (w > PACE_WMAX) w = PACE_WMAX;
            if (i >= n_v && w > win[i] + TAIL_UP) w = win[i] + TAIL_UP;
            for (int j = i - 1; j >= 0; j--)
                if (cum[i + 1] - cum[j] > w) { wd = order[j]; break; }
            lv |= (unsigned long long)wd << (8 * l);
        }
        op[i].z = (unsigned)lv;
        op[i].w = (unsigned)(lv >> 32);
        if (i >= NPRE) list[i - NPRE] = op[i];
    }
}

}

extern "C" void kernel_launch(void* const* d_in, const int* in_sizes, int n_in, void* d_out, int out_size) {
    (void)in_sizes; (void)n_in; (void)out_size;
    const __nv_bfloat16* x = (const __nv_bfloat16*)d_in[0];
    const __nv_bfloat16* kc = (const __nv_bfloat16*)d_in[1];
    const __nv_bfloat16* vc = (const __nv_bfloat16*)d_in[2];
    const __nv_bfloat16* wq = (const __nv_bfloat16*)d_in[3];
    const __nv_bfloat16* wo = (const __nv_bfloat16*)d_in[4];
    const __nv_bfloat16* wg = (const __nv_bfloat16*)d_in[6];
    const __nv_bfloat16* wu = (const __nv_bfloat16*)d_in[7];
    const __nv_bfloat16* wd = (const __nv_bfloat16*)d_in[8];
    const __nv_bfloat16* cv = (const __nv_bfloat16*)d_in[9];
    const __nv_bfloat16* wm = (const __nv_bfloat16*)d_in[10];

    EncodeFn enc = nullptr;
    cudaDriverEntryPointQueryResult qr;
    cudaGetDriverEntryPoint("cuTensorMapEncodeTiled", (void**)&enc, cudaEnableDefault, &qr);
    cudaFuncSetAttribute(fused_block_kernel, cudaFuncAttributeMaxDynamicSharedMemorySize, SMEM_BYTES);
    Params mp;
    const CUtensorMapL2promotion P128 = CU_TENSOR_MAP_L2_PROMOTION_L2_128B, P256 = CU_TENSOR_MAP_L2_PROMOTION_L2_256B;
    make_map(enc, &mp.m[M_WMOD], wm, 6 * DM, DM, 32, 192, CU_TENSOR_MAP_SWIZZLE_64B, P128);
    make_map(enc, &mp.m[M_WQ], wq, 4096, DM, 32, 192, CU_TENSOR_MAP_SWIZZLE_64B, P128);
    make_map(enc, &mp.m[M_K], kc, 128, (uint64_t)2 * 16 * SK, 128, 32, CU_TENSOR_MAP_SWIZZLE_NONE, P256);
    make_map(enc, &mp.m[M_V], vc, 128, (uint64_t)2 * 16 * SK, 64, 32, CU_TENSOR_MAP_SWIZZLE_128B, P256, true);
    make_map(enc, &mp.m[M_WO], wo, 64, 4096 * 9, 64, 72, CU_TENSOR_MAP_SWIZZLE_128B, P256);
    make_map(enc, &mp.m[M_DN], wd, 64, FF * 9, 64, 72, CU_TENSOR_MAP_SWIZZLE_128B, P256);
    make_map(enc, &mp.m[M_GATE], wg, FF, DM, 32, 192, CU_TENSOR_MAP_SWIZZLE_64B, P128);
    make_map(enc, &mp.m[M_UP], wu, FF, DM, 32, 192, CU_TENSOR_MAP_SWIZZLE_64B, P128);
    make_map(enc, &mp.m[M_GATEX], wg, FF, DM, 16, 192, CU_TENSOR_MAP_SWIZZLE_32B, P128);
    make_map(enc, &mp.m[M_UPX], wu, FF, DM, 16, 192, CU_TENSOR_MAP_SWIZZLE_32B, P128);
    build_ops(mp.op, false, mp.nom);
    build_ops(mp.op + NOPS_LIGHT, true, nullptr);
    for (int i = 3; i < 9; i++) {
        const int blk = i / 3, bar = (blk == 1 ? U_WQ : 3) + i % 3;
        mp.op[NOPS_LIGHT + NOPS_HEAVY + i - 3] =
            make_uint4(((OFF_WMOD + i * 12288) >> 8) | ((blk + 1) << 10) | (M_WMOD << 15) | (12 << 19) | (bar << 24),
                       (i % 3) * 192 | (B_DONE << 12), B_DONE * 0x01010101u, B_DONE * 0x01010101u);
    }
    Scratch* gs = nullptr;
    cudaGetSymbolAddress((void**)&gs, g_scratch);
    fused_block_kernel<<<NCTA + NHELP, NTHR, SMEM_BYTES>>>(x, cv, (__nv_bfloat16*)d_out, gs, (const char*)kc, mp);
}
```

```cpp
#include <cuda_runtime.h>
#include <cuda.h>
#include <cuda_bf16.h>
#include <stdint.h>

namespace {

constexpr int DM = 576;
constexpr int FF = 4608;
constexpr int SK = 32768;
constexpr int WIN = 4096;
constexpr int NCTA = 128;
constexpr int NHELP = 4;
constexpr int NTHR = 384;
constexpr int NRED = 36;
constexpr int RED_WARP = 8;

constexpr int WIN_MID = 40, WIN_END = 48, WIN_TAIL = 32, WIN_LAST = 36;
constexpr int WIN_HEAVY_EXTRA = 12, END_CHUNKS = 8;
constexpr int PACE_T0 = -500, PACE_TV = 23100, PACE_TV_HEAVY = 22900, PACE_TE = 29600;
constexpr int PACE_MID = 3, PACE_STEP = 8, PACE_SHIFT = 8;
constexpr int PACE_WMIN = 18, PACE_WMAX = 64, TAIL_UP = 8;
constexpr int ANCHOR_BACK = 8, ANCHOR_BIAS = 650;
constexpr int K_AT_START = 2;
constexpr int REP1 = 8;
constexpr int RCNT = 8, RCNT0 = 4;
constexpr unsigned HINT_MOD = 36, HINT_AO = 112, HINT_X1 = 28;
constexpr int PREWRITE_AT = 54;
constexpr int SLEEP_NS = 100;
constexpr unsigned SPIN_LIMIT = 1u << 22;

constexpr int CH = 8192;
constexpr int NS = 26;
constexpr int S0 = 14;
constexpr int OFF_WMOD = 40960;
constexpr int OFF_WQ = 77824;
constexpr int OFF_WO = 0;
constexpr int OFF_GU = 36864;
constexpr int OFF_GX = 110592;
constexpr int OFF_DN = 147456;
constexpr int OFF_SC = NS * CH;
constexpr int OFF_P = OFF_SC + 8192;
constexpr int OFF_Q = OFF_P + 4096;
constexpr int OFF_ST = OFF_Q + 512;
constexpr int OFF_HH = OFF_ST + 256;
constexpr int OFF_R2 = OFF_HH + 256;
constexpr int OFF_OB = OFF_R2 + 1024;
constexpr int OFF_BAR = OFF_OB + 128;
constexpr int SMEM_BYTES = OFF_BAR + 192 * 8 + 1024;
static_assert(SMEM_BYTES <= 232448, "smem");

constexpr int U_KV = 3;
constexpr int U_WO = 67;
constexpr int U_GU = 71;
constexpr int U_WQ = 80;
constexpr int U_GX = 83;
constexpr int U_DN = 89;
constexpr int B_DONE = 95;
constexpr int B_MODFREE = 96, B_WQFREE = 97;
constexpr int B_GATE_AO = 98, B_GATE_X1 = 99, B_GATE_MOD = 100;
constexpr int B_USED = 128;

enum { M_WMOD, M_WQ, M_K, M_V, M_WO, M_DN, M_GATE, M_UP, M_GATEX, M_UPX, M_COUNT };
constexpr int NPRE = 3 + K_AT_START;
constexpr int NOPS_LIGHT = 84 - NPRE, NOPS_HEAVY = 89 - NPRE, NOPS_HELP = 6;
struct Params { CUtensorMap m[M_COUNT]; uint4 op[NOPS_LIGHT + NOPS_HEAVY + NOPS_HELP]; };

static_assert(sizeof(Params) + 64 <= 4096, "kernel parameters");

enum { C_AO, C_X1, C_UNUSED, C_MOD, C_COUNT };
struct __align__(128) Scratch {
    unsigned int epoch;
    unsigned int pad[31];
    unsigned int cnt[3][C_COUNT][RCNT][32];
    unsigned long long ex_mod[REP1 * 6 * DM];
    unsigned long long ex_q[2 * 2048];
    unsigned long long ex_x1[DM];
    unsigned long long ex_ml[NCTA * 4];
    uint32_t ex_o[NCTA * 256];
    uint32_t ex_part[NCTA * DM * 2];
};
__device__ Scratch g_scratch;

__device__ __forceinline__ uint32_t fu(float x) { return __float_as_uint(x); }
__device__ __forceinline__ float uf(uint32_t x) { return __uint_as_float(x); }
__device__ __forceinline__ uint32_t now_ns() { uint32_t t; asm volatile("mov.u32 %0, %globaltimer_lo;" : "=r"(t)); return t; }
__device__ __forceinline__ void mbar_init(uint32_t b, int c) {
    asm volatile("mbarrier.init.shared::cta.b64 [%0], %1;" ::"r"(b), "r"(c) : "memory");
}
__device__ __forceinline__ void mbar_init_fence() { asm volatile("fence.mbarrier_init.release.cluster;" ::: "memory"); }
__device__ __forceinline__ void mbar_expect(uint32_t b, uint32_t bytes) {
    asm volatile("mbarrier.arrive.expect_tx.shared::cta.b64 _, [%0], %1;" ::"r"(b), "r"(bytes) : "memory");
}
__device__ __forceinline__ void mbar_arrive_if(uint32_t b, uint32_t cnt, bool p) {
    asm volatile("{\n.reg .pred p;\nsetp.ne.u32 p, %2, 0;\n@p mbarrier.arrive.shared::cta.b64 _, [%0], %1;\n}"
                 ::"r"(b), "r"(cnt), "r"((uint32_t)p) : "memory");
}
__device__ __forceinline__ bool mbar_try(uint32_t b) {
    uint32_t ok;
    asm volatile("{\n.reg .pred p;\nmbarrier.try_wait.parity.shared::cta.b64 p, [%1], 0;\nselp.u32 %0, 1, 0, p;\n}"
                 : "=r"(ok) : "r"(b) : "memory");
    return ok;
}
__device__ __forceinline__ bool mbar_test(uint32_t b) {
    uint32_t ok;
    asm volatile("{\n.reg .pred p;\nmbarrier.test_wait.parity.shared::cta.b64 p, [%1], 0;\nselp.u32 %0, 1, 0, p;\n}"
                 : "=r"(ok) : "r"(b) : "memory");
    return ok;
}
__device__ __forceinline__ void mbar_wait(uint32_t b) {
    unsigned n = 0;
    while (!mbar_try(b))
        if (++n > SPIN_LIMIT) __trap();
}
__device__ __forceinline__ void tma3d(uint32_t dst, const CUtensorMap* m, int c0, int c1, uint32_t bar) {
    asm volatile("cp.async.bulk.tensor.3d.shared::cluster.global.mbarrier::complete_tx::bytes [%0], [%1, {%3, %4, %5}], [%2];"
                 ::"r"(dst), "l"(m), "r"(bar), "r"(c0), "r"(c1), "r"(0) : "memory");
}
__device__ __forceinline__ void tma3d_hint(uint32_t dst, const CUtensorMap* m, int c0, int c1, uint32_t bar, uint64_t pol) {
    asm volatile("cp.async.bulk.tensor.3d.shared::cluster.global.mbarrier::complete_tx::bytes.L2::cache_hint [%0], [%1, {%3, %4, %5}], [%2], %6;"
                 ::"r"(dst), "l"(m), "r"(bar), "r"(c0), "r"(c1), "r"(0), "l"(pol) : "memory");
}
__device__ __forceinline__ bool elect_one() {
    uint32_t p;
    asm volatile("{\n.reg .pred p;\nelect.sync _|p, 0xffffffff;\nselp.u32 %0, 1, 0, p;\n}" : "=r"(p));
    return p;
}
__device__ __forceinline__ uint32_t ldg32(const void* p) {
    uint32_t v;
    asm volatile("ld.global.nc.u32 %0, [%1];" : "=r"(v) : "l"(p));
    return v;
}
__device__ __forceinline__ void bar_comp() { asm volatile("bar.sync 1, 288;" ::: "memory"); }
__device__ __forceinline__ void bar_256() { asm volatile("bar.sync 2, 256;" ::: "memory"); }
__device__ __forceinline__ void sts16(uint32_t a, uint32_t v) { asm volatile("st.shared.b16 [%0], %1;" ::"r"(a), "h"((unsigned short)v) : "memory"); }
__device__ __forceinline__ void sts32_if(uint32_t a, uint32_t v, bool p) {
    asm volatile("{\n.reg .pred p;\nsetp.ne.u32 p, %2, 0;\n@p st.shared.b32 [%0], %1;\n}" ::"r"(a), "r"(v), "r"((uint32_t)p) : "memory");
}
__device__ __forceinline__ void sts64_if(uint32_t a, uint32_t v0, uint32_t v1, bool p) {
    asm volatile("{\n.reg .pred p;\nsetp.ne.u32 p, %3, 0;\n@p st.shared.v2.b32 [%0], {%1, %2};\n}" ::"r"(a), "r"(v0), "r"(v1), "r"((uint32_t)p) : "memory");
}
__device__ __forceinline__ void sts128_if(uint32_t a, uint32_t v0, uint32_t v1, uint32_t v2, uint32_t v3, bool p) {
    asm volatile("{\n.reg .pred p;\nsetp.ne.u32 p, %5, 0;\n@p st.shared.v4.b32 [%0], {%1, %2, %3, %4};\n}"
                 ::"r"(a), "r"(v0), "r"(v1), "r"(v2), "r"(v3), "r"((uint32_t)p) : "memory");
}
__device__ __forceinline__ float lds_f(uint32_t a) { float v; asm volatile("ld.shared.f32 %0, [%1];" : "=f"(v) : "r"(a) : "memory"); return v; }
__device__ __forceinline__ float2 lds_f2(uint32_t a) {
    float2 v; asm volatile("ld.shared.v2.f32 {%0,%1}, [%2];" : "=f"(v.x), "=f"(v.y) : "r"(a) : "memory"); return v;
}
__device__ __forceinline__ float4 lds_f4(uint32_t a) {
    float4 v; asm volatile("ld.shared.v4.f32 {%0,%1,%2,%3}, [%4];" : "=f"(v.x), "=f"(v.y), "=f"(v.z), "=f"(v.w) : "r"(a) : "memory"); return v;
}
__device__ __forceinline__ uint4 lds128(uint32_t addr) {
    uint4 v;
    asm volatile("ld.shared.v4.u32 {%0,%1,%2,%3}, [%4];" : "=r"(v.x), "=r"(v.y), "=r"(v.z), "=r"(v.w) : "r"(addr) : "memory");
    return v;
}
__device__ __forceinline__ void ldsm4t(uint32_t (&a)[4], uint32_t addr) {
    asm volatile("ldmatrix.sync.aligned.m8n8.x4.trans.shared.b16 {%0,%1,%2,%3}, [%4];"
                 : "=r"(a[0]), "=r"(a[1]), "=r"(a[2]), "=r"(a[3]) : "r"(addr) : "memory");
}
__device__ __forceinline__ void mma(float (&c)[4], uint32_t a0, uint32_t a1, uint32_t a2, uint32_t a3, uint32_t b0, uint32_t b1) {
    asm volatile("mma.sync.aligned.m16n8k16.row.col.f32.bf16.bf16.f32 {%0,%1,%2,%3}, {%4,%5,%6,%7}, {%8,%9}, {%0,%1,%2,%3};"
                 : "+f"(c[0]), "+f"(c[1]), "+f"(c[2]), "+f"(c[3])
                 : "r"(a0), "r"(a1), "r"(a2), "r"(a3), "r"(b0), "r"(b1));
}
__device__ __forceinline__ void mma(float (&c)[4], const uint32_t (&a)[4], uint32_t b0, uint32_t b1) {
    mma(c, a[0], a[1], a[2], a[3], b0, b1);
}

template <bool ATOM>
__device__ __forceinline__ void rd16(unsigned long long& a, unsigned long long& b, const void* p, uint32_t on) {
    if (ATOM)
        asm volatile("{\n.reg .pred p;\n.reg .b128 z, d;\nsetp.ne.u32 p, %3, 0;\nmov.b128 z, {0, 0};\nmov.b128 d, {%0, %1};\n"
                     "@p atom.relaxed.gpu.global.cas.b128 d, [%2], z, z;\nmov.b128 {%0, %1}, d;\n}"
                     : "+l"(a), "+l"(b) : "l"(p), "r"(on) : "memory");
    else
        asm volatile("{\n.reg .pred p;\nsetp.ne.u32 p, %3, 0;\n@p ld.relaxed.gpu.global.v2.b64 {%0, %1}, [%2];\n}"
                     : "+l"(a), "+l"(b) : "l"(p), "r"(on) : "memory");
}
__device__ __forceinline__ void st_w1(unsigned long long* p, uint32_t v, uint32_t tag, bool on) {
    unsigned long long w = ((unsigned long long)tag << 32) | v;
    asm volatile("{\n.reg .pred p;\nsetp.ne.u32 p, %2, 0;\n@p st.relaxed.gpu.global.b64 [%0], %1;\n}" ::"l"(p), "l"(w), "r"((uint32_t)on) : "memory");
}
__device__ __forceinline__ void st_w2(unsigned long long* p, uint32_t v0, uint32_t v1, uint32_t tag, bool on) {
    unsigned long long w0 = ((unsigned long long)tag << 32) | v0, w1 = ((unsigned long long)tag << 32) | v1;
    asm volatile("{\n.reg .pred p;\nsetp.ne.u32 p, %3, 0;\n@p st.relaxed.gpu.global.v2.b64 [%0], {%1, %2};\n}"
                 ::"l"(p), "l"(w0), "l"(w1), "r"((uint32_t)on) : "memory");
}
template <int N, bool ATOM>
__device__ __forceinline__ void poll2(const unsigned long long* p, const int (&off)[N], uint32_t (&v)[2 * N], uint32_t tag, bool on) {
    unsigned long long w[2 * N];
    uint32_t need[N];
#pragma unroll
    for (int i = 0; i < N; i++) { w[2 * i] = w[2 * i + 1] = (unsigned long long)tag << 32; need[i] = on; }
    unsigned n = 0;
    while (true) {
#pragma unroll
        for (int i = 0; i < N; i++) rd16<ATOM>(w[2 * i], w[2 * i + 1], p + off[i], need[i]);
        uint32_t any = 0;
#pragma unroll
        for (int i = 0; i < N; i++) {
            need[i] = ((uint32_t)(w[2 * i] >> 32) ^ tag) | ((uint32_t)(w[2 * i + 1] >> 32) ^ tag);
            any |= need[i];
        }
        if (!__any_sync(0xffffffffu, any != 0)) break;
        __nanosleep(SLEEP_NS);
        if (++n > SPIN_LIMIT) __trap();
    }
#pragma unroll
    for (int i = 0; i < 2 * N; i++) v[i] = (uint32_t)w[i];
}
__device__ __forceinline__ uint32_t tagf(float v, uint32_t tg) { return (fu(v) & ~3u) | tg; }
__device__ __forceinline__ void st_t1(uint32_t* p, uint32_t v) {
    asm volatile("st.relaxed.gpu.global.b32 [%0], %1;" ::"l"(p), "r"(v) : "memory");
}
__device__ __forceinline__ void st_t4(uint32_t* p, uint32_t a, uint32_t b, uint32_t c, uint32_t d) {
    asm volatile("st.relaxed.gpu.global.v4.b32 [%0], {%1, %2, %3, %4};" ::"l"(p), "r"(a), "r"(b), "r"(c), "r"(d) : "memory");
}
template <int N, int STRIDE, bool ATOM>
__device__ __forceinline__ void poll_lines(const uint32_t* p, float (&v)[N], uint32_t tg) {
    uint32_t w[N];
#pragma unroll
    for (int i = 0; i < N; i++) w[i] = 0;
    unsigned n = 0;
    while (true) {
#pragma unroll
        for (int i = 0; i < N; i++) {
            if (ATOM)
                asm volatile("{\n.reg .pred p;\nsetp.ne.u32 p, %2, 0;\n@p atom.relaxed.gpu.global.or.b32 %0, [%1], 0;\n}"
                             : "+r"(w[i]) : "l"(p + i * STRIDE), "r"((w[i] ^ tg) & 3u) : "memory");
            else
                asm volatile("{\n.reg .pred p;\nsetp.ne.u32 p, %2, 0;\n@p ld.relaxed.gpu.global.b32 %0, [%1];\n}"
                             : "+r"(w[i]) : "l"(p + i * STRIDE), "r"((w[i] ^ tg) & 3u) : "memory");
        }
        uint32_t any = 0;
#pragma unroll
        for (int i = 0; i < N; i++) any |= w[i] ^ tg;
        if (!__any_sync(0xffffffffu, (any & 3u) != 0)) break;
        if (++n > SPIN_LIMIT) __trap();
    }
#pragma unroll
    for (int i = 0; i < N; i++) v[i] = uf(w[i] & ~3u);
}
__device__ __forceinline__ void announce(unsigned int* c, bool on) {
    if (on) asm volatile("red.relaxed.gpu.global.add.u32 [%0], 1;" ::"l"(c) : "memory");
}
template <bool SLEEP>
__device__ __forceinline__ void await_count(const unsigned int* p, unsigned target, uint32_t gate, int lane) {
    unsigned n = 0, c;
    while (true) {
        c = 0;
        if (lane == 0) asm volatile("atom.relaxed.gpu.global.or.b32 %0, [%1], 0;" : "=r"(c) : "l"(p) : "memory");
        c = __shfl_sync(0xffffffffu, c, 0);
        if (c >= target) break;
        if (SLEEP) __nanosleep(SLEEP_NS);
        if (++n > SPIN_LIMIT) __trap();
    }
    mbar_arrive_if(gate, 1, lane == 0);
}

__device__ __forceinline__ float rbf(float x) {
    uint32_t r;
    asm("cvt.rn.bf16x2.f32 %0, %1, 0f00000000;" : "=r"(r) : "f"(x));
    return uf(r);
}
__device__ __forceinline__ uint32_t pack2(float lo, float hi) {
    __nv_bfloat162 v = __floats2bfloat162_rn(lo, hi);
    return *reinterpret_cast<uint32_t*>(&v);
}
__device__ __forceinline__ float bf_lo(uint32_t v) { return uf(v << 16); }
__device__ __forceinline__ float bf_hi(uint32_t v) { return uf(v & 0xffff0000u); }
__device__ __forceinline__ float bf_sel(uint32_t v, int hi) { return hi ? bf_hi(v) : bf_lo(v); }
__device__ __forceinline__ float sel4(int t, float a, float b, float c, float d) {
    return (t & 2) ? ((t & 1) ? d : c) : ((t & 1) ? b : a);
}

__device__ __forceinline__ void ln_part1(const float (&v)[4], uint32_t stats, int warp, int lane) {
    float mean = 0.25f * ((v[0] + v[1]) + (v[2] + v[3]));
    float m2;
    { float a = v[0] - mean, b = v[1] - mean, c = v[2] - mean, d = v[3] - mean; m2 = (a * a + b * b) + (c * c + d * d); }
    float cnt_half = 2.f;
#pragma unroll
    for (int s = 0; s < 4; s++) {
        const int mask = (s == 0) ? 1 : (s == 1) ? 2 : (s == 2) ? 8 : 16;
        const float om = __shfl_xor_sync(0xffffffffu, mean, mask);
        const float o2 = __shfl_xor_sync(0xffffffffu, m2, mask);
        const float d = om - mean;
        m2 = (m2 + o2) + d * d * cnt_half;
        mean = 0.5f * (mean + om);
        cnt_half *= 2.f;
    }
    sts64_if(stats + ((lane >> 2) & 1) * 80 + warp * 8, fu(mean), fu(m2), (lane & ~4) == 0);
}
__device__ __forceinline__ void ln_part2(float (&v)[4], uint32_t stats, int lane) {
    const uint32_t st = stats + ((lane >> 2) & 1) * 80;
    const float4 a = lds_f4(st), b = lds_f4(st + 16), c = lds_f4(st + 32), d = lds_f4(st + 48);
    const float2 e = lds_f2(st + 64);
    const float mu = ((((a.x + a.z) + (b.x + b.z)) + ((c.x + c.z) + (d.x + d.z))) + e.x) * (1.f / 9.f);
    const float M2 = (((a.y + a.w) + (b.y + b.w)) + ((c.y + c.w) + (d.y + d.w))) + e.y;
    const float q0 = a.x - mu, q1 = a.z - mu, q2 = b.x - mu, q3 = b.z - mu, q4 = c.x - mu, q5 = c.z - mu, q6 = d.x - mu,
                q7 = d.z - mu, q8 = e.x - mu;
    const float dd = (((q0 * q0 + q1 * q1) + (q2 * q2 + q3 * q3)) + ((q4 * q4 + q5 * q5) + (q6 * q6 + q7 * q7))) + q8 * q8;
    const float mb = rbf(mu);
    const float vb = rbf((M2 + 64.f * dd) * (1.f / 576.f));
    float sq, rd;
    asm("sqrt.approx.f32 %0, %1;" : "=f"(sq) : "f"(rbf(vb + 1e-5f)));
    asm("rcp.approx.f32 %0, %1;" : "=f"(rd) : "f"(rbf(sq)));
#pragma unroll
    for (int i = 0; i < 4; i++) v[i] = rbf(rbf(v[i] - mb) * rd);
}

__device__ __forceinline__ void spread_b(uint32_t (&b)[4][2], uint32_t r0, uint32_t r1, int lane) {
#pragma unroll
    for (int ks = 0; ks < 4; ks++) {
        const int src = (ks << 3) | (lane & 7);
        b[ks][0] = __shfl_sync(0xffffffffu, r0, src);
        b[ks][1] = __shfl_sync(0xffffffffu, r1, src);
    }
}

__device__ __noinline__ void gemv32(uint32_t tile, uint32_t bar, uint32_t r0, uint32_t r1, uint32_t red, int warp) {
    const int lane = threadIdx.x & 31;
    uint32_t b[4][2];
    spread_b(b, r0, r1, lane);
    float acc[2][4] = {};
    const int rr = (lane & 7) + ((lane >> 4) << 3);
    const uint32_t a0 = tile + (warp * 64 + rr) * 64;
    const int sw = (rr >> 1) & 3, c = (lane >> 3) & 1;
    mbar_wait(bar + 8 * (warp / 3));
#pragma unroll
    for (int ks = 0; ks < 4; ks++) {
#pragma unroll
        for (int mt = 0; mt < 2; mt++) {
            uint32_t a[4];
            ldsm4t(a, a0 + ks * 1024 + (((mt * 2 + c) ^ sw) << 4));
            mma(acc[mt], a, b[ks][0], b[ks][1]);
        }
    }
    const int t = lane & 3, g = lane >> 2;
    sts64_if(red + (warp * 32 + t * 8 + g) * 8, fu(sel4(t, acc[0][0], acc[0][2], acc[1][0], acc[1][2])),
             fu(sel4(t, acc[0][1], acc[0][3], acc[1][1], acc[1][3])), true);
}
__device__ __forceinline__ float2 sum9(uint32_t red) {
    float2 v[9];
#pragma unroll
    for (int w = 0; w < 9; w++) v[w] = lds_f2(red + w * 256);
    return make_float2((((v[0].x + v[1].x) + (v[2].x + v[3].x)) + ((v[4].x + v[5].x) + (v[6].x + v[7].x))) + v[8].x,
                       (((v[0].y + v[1].y) + (v[2].y + v[3].y)) + ((v[4].y + v[5].y) + (v[6].y + v[7].y))) + v[8].y);
}

__device__ __forceinline__ void reduce_part1(const uint32_t* p, uint32_t r2, int warp, int lane, uint32_t tg) {
    float v[16];
    poll_lines<16, DM * 2, false>(p, v, tg);
    const float s = (((v[0] + v[1]) + (v[2] + v[3])) + ((v[4] + v[5]) + (v[6] + v[7]))) +
                    (((v[8] + v[9]) + (v[10] + v[11])) + ((v[12] + v[13]) + (v[14] + v[15])));
    sts32_if(r2 + (warp * 32 + (lane >> 2) + (lane & 2) * 4 + (lane & 1) * 16) * 4, fu(s), true);
}
__device__ __forceinline__ float reduce_part2(uint32_t r2, int lane) {
    float a[8];
#pragma unroll
    for (int w = 0; w < 8; w++) a[w] = lds_f(r2 + (w * 32 + lane) * 4);
    return ((a[0] + a[1]) + (a[2] + a[3])) + ((a[4] + a[5]) + (a[6] + a[7]));
}
__device__ __forceinline__ uint32_t next_epoch(const Scratch* gs) {
    uint32_t e;
    asm volatile("ld.relaxed.gpu.global.u32 %0, [%1];" : "=r"(e) : "l"(&gs->epoch) : "memory");
    return e >= 0x7ffffffeu ? 1u : e + 1;
}

__global__ void __launch_bounds__(NTHR, 1)
fused_block_kernel(const __nv_bfloat16* __restrict__ x, const __nv_bfloat16* __restrict__ cvec, __nv_bfloat16* __restrict__ out,
                   Scratch* __restrict__ gs, const char* __restrict__ kbytes, const __grid_constant__ Params mp)
{
    extern __shared__ __align__(1024) unsigned char smem_raw[];
    const uint32_t base = ((uint32_t)__cvta_generic_to_shared(smem_raw) + 1023u) & ~1023u;
    const uint32_t bars = base + OFF_BAR;
    const bool helper = blockIdx.x < NHELP;
    const int cta = helper ? NCTA + blockIdx.x : blockIdx.x - NHELP;
    const bool heavy = cta >= 96;
    const int mblk0 = helper ? 96 + 3 * blockIdx.x : cta;
    const int krow = ((((cta >> 2) & 1) * 16 + (cta >> 3)) * SK + (SK - WIN)) + (cta & 3) * 64;
    if (!helper && threadIdx.x < 128) asm volatile("prefetch.global.L2 [%0];" ::"l"(kbytes + (size_t)krow * 256 + threadIdx.x * 128));
    uint32_t t_start = now_ns();

    if (threadIdx.x >= 320) {
        const int lane = threadIdx.x & 31, warp = __shfl_sync(0xffffffffu, threadIdx.x >> 5, 0);
        const int nops = helper ? NOPS_HELP : heavy ? NOPS_HEAVY : NOPS_LIGHT;
        uint4 tab0 = make_uint4(0, 0, 0, 0), tab1 = tab0;
        {
            const uint4* ops = mp.op + (helper ? NOPS_LIGHT + NOPS_HEAVY : heavy ? NOPS_LIGHT : 0);
            const int i0 = (warp & 1) + 2 * lane;
            if (i0 < nops) asm volatile("ld.v4.u32 {%0,%1,%2,%3}, [%4];" : "=r"(tab0.x), "=r"(tab0.y), "=r"(tab0.z), "=r"(tab0.w) : "l"(ops + i0));
            if (i0 + 64 < nops) asm volatile("ld.v4.u32 {%0,%1,%2,%3}, [%4];" : "=r"(tab1.x), "=r"(tab1.y), "=r"(tab1.z), "=r"(tab1.w) : "l"(ops + i0 + 64));
        }
        if (warp == 10 && lane >= 1 && lane < M_COUNT) asm volatile("prefetch.tensormap [%0];" ::"l"(&mp.m[lane]) : "memory");
        const int xcol = 4096 + (cta - 96) * 16;
        const int base0 = helper ? (mblk0 + lane - 1) * 32 : lane == 1 ? cta * 32 : lane == 2 ? xcol : 0;
        const int base1 = lane == 1 ? krow : lane == 4 ? cta * 288 : lane == 5 ? xcol * 9 : 0;
        uint64_t pol;
        asm volatile("createpolicy.fractional.L2::evict_first.b64 %0, 1.0;" : "=l"(pol));
        const int cnt = (nops + 1 - (warp & 1)) >> 1;
        asm volatile("bar.sync 3, 384;" ::: "memory");
#pragma unroll 1
        for (int k = 0; k < cnt; k++) {
            if (k == 32) tab0 = tab1;
            uint4 e;
            e.x = __shfl_sync(0xffffffffu, tab0.x, k); e.y = __shfl_sync(0xffffffffu, tab0.y, k);
            e.z = __shfl_sync(0xffffffffu, tab0.z, k); e.w = __shfl_sync(0xffffffffu, tab0.w, k);
            const uint32_t bar = bars + (e.x >> 24) * 8;
            const int c0 = __shfl_sync(0xffffffffu, base0, (e.x >> 10) & 3);
            const int c1 = (e.y & 0xfff) + __shfl_sync(0xffffffffu, base1, (e.x >> 12) & 7);
            const uint32_t dst = base + (e.x & 0x3ff) * 256;
            const CUtensorMap* map = &mp.m[(e.x >> 15) & 15];
            mbar_wait(bars + ((e.y >> 12) & 0xff) * 8);
            if (lane == 0) mbar_expect(bar, ((e.x >> 19) & 15) << 10);
            if (e.x & (1u << 23)) {
                const int lag = (int)(now_ns() - (t_start + (e.y >> 20) * 16)) + ANCHOR_BIAS;
                if (lag > 0) t_start += lag;
            }
            const uint32_t due = t_start + (e.y >> 20) * 16;
            unsigned n = 0;
            while (true) {
                const int lvl = min(max(PACE_MID + ((int)(now_ns() - due) >> PACE_SHIFT), 0), 7);
                if (mbar_test(bars + (__byte_perm(e.z, e.w, lvl) & 0xff) * 8)) break;
                if (++n > 64 * SPIN_LIMIT) __trap();
            }
            if (lane == 0) tma3d_hint(dst, map, c0, c1, bar, pol);
            __syncwarp();
        }
        return;
    }

    if (threadIdx.x == 32 && !helper) {
#pragma unroll
        for (int i = 0; i < K_AT_START; i++) mbar_init(bars + 8 * (U_KV + i), 1);
        mbar_init_fence();
#pragma unroll
        for (int i = 0; i < K_AT_START; i++) {
            mbar_expect(bars + 8 * (U_KV + i), CH);
            asm volatile("cp.async.bulk.shared::cluster.global.mbarrier::complete_tx::bytes [%0], [%1], %2, [%3];"
                         ::"r"(base + (S0 + i) * CH), "l"(kbytes + (size_t)krow * 256 + i * CH), "r"(CH), "r"(bars + 8 * (U_KV + i)) : "memory");
        }
    }
    if (threadIdx.x == 0) {
        const bool q1 = heavy && !helper;
        const uint32_t bb = bars + (q1 ? 8 * U_WQ : 0), dst = base + (q1 ? OFF_WQ : OFF_WMOD);
#pragma unroll
        for (int i = 0; i < 3; i++) { mbar_init(bars + 8 * i, 1); mbar_init(bars + 8 * (U_WQ + i), 1); }
        mbar_init_fence();
#pragma unroll
        for (int i = 0; i < 3; i++) {
            mbar_expect(bb + 8 * i, 12288);
            tma3d(dst + i * 12288, &mp.m[q1 ? M_WQ : M_WMOD], mblk0 * 32, i * 192, bb + 8 * i);
        }
    }
    int tid;
    asm volatile("mov.u32 %0, %tid.x;" : "=r"(tid));
    const int lane = tid & 31;
    const int warp = __shfl_sync(0xffffffffu, tid >> 5, 0);
    if (elect_one()) {
        if (warp < 7) {
            const uint32_t b0 = bars + warp * 128;
            if (warp != 0 && warp != 5) {
#pragma unroll
                for (int i = 0; i < 3; i++) mbar_init(b0 + 8 * i, 1);
            }
            if (warp != 6) {
#pragma unroll
                for (int i = 6; i < 16; i++) mbar_init(b0 + 8 * i, 1);
            }
#pragma unroll
            for (int i = 3; i < 6; i++)
                if (i >= 3 + K_AT_START || warp != 0 || helper) mbar_init(b0 + 8 * i, 1);
            mbar_arrive_if(bars + 8 * B_DONE, 1, warp == 5);
        }
        if (warp >= 6) {
#pragma unroll
            for (int i = 0; i < 16; i++) mbar_init(bars + 8 * (B_USED + (warp - 6) * 16 + i), 8);
        }
        mbar_init_fence();
    }
    __syncwarp();
    asm volatile("bar.arrive 3, 384;\nbar.sync 8, 320;" ::: "memory");

    if (warp == 9) {
        if (helper) return;
        const uint32_t ep = next_epoch(gs);
        unsigned int (*cnt)[RCNT][32] = gs->cnt[ep % 3];
        if (cta < C_COUNT && lane < RCNT) st_t1(&gs->cnt[(ep + 1) % 3][cta][lane][0], 0u);
        await_count<true>(cnt[C_MOD][cta % RCNT], HINT_MOD, bars + 8 * B_GATE_MOD, lane);
        mbar_wait(bars + 8 * (U_KV + 63));
        {
            float v[8];
            poll_lines<8, 256, true>(gs->ex_o + (cta & ~7) * 256 + (cta & 7) * 32 + lane, v, 1 + ep % 3);
            const float o0 = (v[0] + v[1]) + (v[2] + v[3]), o1 = (v[4] + v[5]) + (v[6] + v[7]);
            const float r = __shfl_xor_sync(0xffffffffu, (lane & 1) ? o0 : o1, 1);
            const int wi = lane >> 1;
            sts32_if(base + OFF_OB + ((lane & 1) * 16 + (wi & 3) * 4 + (wi >> 2)) * 4, (lane & 1) ? pack2(r, o1) : pack2(o0, r), true);
        }
        asm volatile("bar.arrive 4, 320;" ::: "memory");
#pragma unroll 1
        for (int k = cta < NRED ? C_AO : C_X1; k <= C_X1; k++)
            await_count<false>(cnt[k][cta % (k ? RCNT : RCNT0)], k ? HINT_X1 : HINT_AO, bars + 8 * (B_GATE_AO + k), lane);
        asm volatile("bar.sync 6, 320;" ::: "memory");
#pragma unroll
        for (int h = 0; h < 2; h++) {
            if (h == 0 || heavy) {
                const int ci = h * 32 + (h ? lane & 15 : lane);
                float4 u[9];
#pragma unroll
                for (int w = 0; w < 9; w++) u[w] = lds_f4(base + OFF_SC + (w * 48 + ci) * 16);
                float4 s;
                s.x = (((u[0].x + u[1].x) + (u[2].x + u[3].x)) + ((u[4].x + u[5].x) + (u[6].x + u[7].x))) + u[8].x;
                s.y = (((u[0].y + u[1].y) + (u[2].y + u[3].y)) + ((u[4].y + u[5].y) + (u[6].y + u[7].y))) + u[8].y;
                s.z = (((u[0].z + u[1].z) + (u[2].z + u[3].z)) + ((u[4].z + u[5].z) + (u[6].z + u[7].z))) + u[8].z;
                s.w = (((u[0].w + u[1].w) + (u[2].w + u[3].w)) + ((u[4].w + u[5].w) + (u[6].w + u[7].w))) + u[8].w;
                float g0 = rbf(s.x), g1 = rbf(s.y);
                g0 = g0 * (g0 > 0.f ? 1.f : 0.f);
                g1 = g1 * (g1 > 0.f ? 1.f : 0.f);
                const uint32_t hp = pack2(g0 * rbf(s.z), g1 * rbf(s.w));
                sts16(base + OFF_HH + ci * 2, hp);
                sts16(base + OFF_HH + 128 + ci * 2, hp >> 16);
            }
        }
        asm volatile("bar.arrive 7, 320;" ::: "memory");
        return;
    }

    const int kvh = cta >> 3, bat = (cta >> 2) & 1;
    const int nmod = helper ? 3 : heavy ? 0 : 1;
    const int g = lane >> 2, t = lane & 3;
    const int fb = g & 1;
    const int col0 = warp * 64 + (g >> 1) * 16 + 2 * t;
    const bool reducer = cta < NRED;
    const int rcol = (reducer ? cta : 0) * 16 + (lane & 15), rb_ = lane >> 4;
    const uint32_t s_sc = base + OFF_SC, s_stats = base + OFF_ST, s_r2 = base + OFF_R2;
    const uint32_t ca_ = ldg32(cvec + fb * DM + col0), cb_ = ldg32(cvec + fb * DM + col0 + 8);
    const uint32_t xa = ldg32(x + fb * DM + col0), xb = ldg32(x + fb * DM + col0 + 8);
    const uint32_t tag = next_epoch(gs);
    const float xr = bf_sel(ldg32(x + rb_ * DM + (rcol & ~1)), lane & 1);
    unsigned int (*cnt)[RCNT][32] = gs->cnt[tag % 3];

    float y[4] = {bf_lo(xa), bf_hi(xa), bf_lo(xb), bf_hi(xb)};
    {
        float cv[4] = {bf_lo(ca_), bf_hi(ca_), bf_lo(cb_), bf_hi(cb_)};
#pragma unroll
        for (int i = 0; i < 4; i++) cv[i] = cv[i] / (1.f + expf(-cv[i]));
        const uint32_t s01 = pack2(cv[0], cv[1]), s23 = pack2(cv[2], cv[3]);
        ln_part1(y, s_stats, warp, lane);
#pragma unroll 1
        for (int m = 0; m < nmod; m++)
            gemv32(base + OFF_WMOD + m * 36864, bars + 8 * (m == 1 ? U_WQ : m == 2 ? 3 : 0), s01, s23, s_sc + m * 2304, warp);
    }
    bar_comp();
    if (warp < nmod) {
        const float2 s2 = sum9(s_sc + warp * 2304 + lane * 8);
#pragma unroll
        for (int r = 0; r < REP1; r++) st_w1(gs->ex_mod + r * 6 * DM + (mblk0 + warp) * 32 + lane, pack2(s2.x, s2.y), tag, true);
        announce(cnt[C_MOD][lane & (RCNT - 1)], cta < 36 && lane < RCNT);
    }
    if (helper) return;
    mbar_arrive_if(bars + 8 * B_MODFREE, 1, tid == 256);
    ln_part2(y, s_stats, lane);
    const int rr = (lane & 7) + ((lane >> 4) << 3), hi8 = (lane >> 3) & 1;
    float cbv[4], sbv[4], gar, gbr;
    const int zoff[1] = {0};
    {
        const unsigned long long* mod = gs->ex_mod + (cta % REP1) * 6 * DM;
        const int moff[4] = {0, 8, DM, DM + 8};
        uint32_t v[8];
        mbar_wait(bars + 8 * B_GATE_MOD);
        poll2<4, false>(mod + col0, moff, v, tag, true);
        float h[4];
#pragma unroll
        for (int i = 0; i < 4; i++) h[i] = rbf(y[i] * rbf(1.f + bf_sel(v[4 + i], fb))) + bf_sel(v[i], fb);
        gemv32(base + OFF_WQ, bars + 8 * U_WQ, pack2(h[0], h[1]), pack2(h[2], h[3]), s_sc + 2304, warp);
        bar_comp();
        if (warp == 0) {
            const float2 s2 = sum9(s_sc + 2304 + lane * 8);
            const float o0 = __shfl_xor_sync(0xffffffffu, s2.x, 1), o1 = __shfl_xor_sync(0xffffffffu, s2.y, 1);
            st_w1(gs->ex_q + (lane & 1) * 2048 + cta * 16 + (lane >> 1), (lane & 1) ? pack2(o1, s2.y) : pack2(s2.x, o0), tag, true);
        }
        mbar_arrive_if(bars + 8 * B_WQFREE, 1, tid == 256);
        poll2<4, false>(mod + 3 * DM + col0, moff, v, tag, true);
#pragma unroll
        for (int i = 0; i < 4; i++) { sbv[i] = bf_sel(v[i], fb); cbv[i] = rbf(1.f + bf_sel(v[4 + i], fb)); }
        if (warp < 2) {
            uint32_t qv[2];
            poll2<1, true>(gs->ex_q + bat * 2048 + kvh * 128 + tid * 2, zoff, qv, tag, true);
            sts64_if(base + OFF_Q + tid * 8, qv[0], qv[1], true);
        }
        bar_comp();
        const int goff[2] = {0, 3 * DM};
        uint32_t gv[4];
        poll2<2, false>(mod + 2 * DM + (rcol & ~1), goff, gv, tag, reducer && warp == RED_WARP);
        gar = bf_sel((lane & 1) ? gv[1] : gv[0], rb_);
        gbr = bf_sel((lane & 1) ? gv[3] : gv[2], rb_);
    }

    const int line0 = rr * 9 + warp;
    const uint32_t rowa = base + line0 * 128;
    const uint32_t lsw = line0 & 7;
    uint32_t wf[4][4][4];
    const uint32_t tg0 = 1 + tag % 3, tg1 = 1 + (2 * (tag % 3)) % 3, tg2 = 1 + (2 * (tag % 3) + 1) % 3;
    unsigned long long* x1dst = gs->ex_x1 + ((lane >> 3) & 1) * 288 + cta * 8 + rb_ * 4 + ((lane >> 1) & 3);
    uint32_t* part = gs->ex_part + cta * (DM * 2) + (warp * 4 + t) * 32 + g * 4;
    const bool x1pub = reducer && warp == RED_WARP && (lane & 1) == 0;
    auto prewrite = [&]() { st_t4(part, 0u, 0u, 0u, 0u); st_w1(x1dst, 0u, 0u, x1pub); };
    auto publish = [&](const float (&acc)[4][4], uint32_t tg) {
        st_t4(part, tagf(sel4(t, acc[0][0], acc[1][0], acc[2][0], acc[3][0]), tg), tagf(sel4(t, acc[0][1], acc[1][1], acc[2][1], acc[3][1]), tg),
              tagf(sel4(t, acc[0][2], acc[1][2], acc[2][2], acc[3][2]), tg), tagf(sel4(t, acc[0][3], acc[1][3], acc[2][3], acc[3][3]), tg));
    };

    if (warp < 8) {
        uint4 qf[4];
#pragma unroll
        for (int j = 0; j < 4; j++) qf[j] = lds128(base + OFF_Q + (g & 1) * 256 + ((j ^ ((g >> 1) & 1)) << 6) + t * 16);
        float mx0 = -INFINITY, mx1 = -INFINITY;
        const uint32_t rowoff = base + ((warp & 1) * 16 + g) * 256 + t * 16;
        const uint32_t sw = (g & 1) << 6;
        const bool valid = (g & 1) == (t & 1);
        uint32_t scp = s_sc + (warp * 16 + g + ((t & 2) << 2)) * 4;
#pragma unroll 1
        for (int c = warp >> 1; c < 32; c += 4) {
            const int s = c + S0 >= NS ? c + S0 - NS : c + S0;
            mbar_wait(bars + 8 * (U_KV + c));
            const uint32_t a0 = rowoff + s * CH;
            float acc[4] = {}, acc2[4] = {};
#pragma unroll
            for (int j = 0; j < 4; j++) {
                const uint32_t o = (j << 6) ^ sw;
                const uint4 lo = lds128(a0 + o), hi = lds128(a0 + 2048 + o);
                mma(acc, lo.x, hi.x, lo.y, hi.y, qf[j].x, qf[j].y);
                mma(acc2, lo.z, hi.z, lo.w, hi.w, qf[j].z, qf[j].w);
            }
            __syncwarp();
            mbar_arrive_if(bars + 8 * (B_USED + c), 4, lane == 0);
            float u0 = (t & 2) ? acc[2] + acc2[2] : acc[0] + acc2[0];
            float u1 = (t & 2) ? acc[3] + acc2[3] : acc[1] + acc2[1];
            u0 = rbf(rbf(u0) * 0.08838834764831845f);
            u1 = rbf(rbf(u1) * 0.08838834764831845f);
            sts32_if(scp, fu(u0), valid);
            sts32_if(scp + 4096, fu(u1), valid);
            mx0 = valid ? fmaxf(mx0, u0) : mx0;
            mx1 = valid ? fmaxf(mx1, u1) : mx1;
            scp += 512;
        }
#pragma unroll
        for (int m = 1; m < 32; m <<= 1) {
            mx0 = fmaxf(mx0, __shfl_xor_sync(0xffffffffu, mx0, m));
            mx1 = fmaxf(mx1, __shfl_xor_sync(0xffffffffu, mx1, m));
        }
        sts64_if(s_stats + warp * 8, fu(mx0), fu(mx1), lane == 0);
        bar_256();
        const int uh = g & 1;
        float mloc = -INFINITY;
#pragma unroll
        for (int w = 0; w < 8; w++) mloc = fmaxf(mloc, lds_f(s_stats + (2 * w + uh) * 4));
        float e[8];
#pragma unroll
        for (int i = 0; i < 4; i++) {
            const float2 v = lds_f2(s_sc + (uh * 1024 + (tid >> 3) * 32 + 2 * t + i * 8) * 4);
            e[2 * i] = __expf(v.x - mloc);
            e[2 * i + 1] = __expf(v.y - mloc);
        }
        float l = ((e[0] + e[1]) + (e[2] + e[3])) + ((e[4] + e[5]) + (e[6] + e[7]));
        l += __shfl_xor_sync(0xffffffffu, l, 1);
        l += __shfl_xor_sync(0xffffffffu, l, 2);
        l += __shfl_xor_sync(0xffffffffu, l, 8);
        l += __shfl_xor_sync(0xffffffffu, l, 16);
        sts32_if(s_stats + (16 + 2 * warp + uh) * 4, fu(l), (lane & ~4) == 0);
        bar_256();
        if (warp == 0) {
            float lt = 0.f;
#pragma unroll
            for (int w = 0; w < 8; w++) lt += lds_f(s_stats + (16 + 2 * w + uh) * 4);
            st_w2(gs->ex_ml + cta * 4 + uh * 2, fu(mloc), fu(lt), tag, (lane & ~4) == 0);
            uint32_t ml[2];
            poll2<1, true>(gs->ex_ml + ((cta & ~3) + t) * 4 + uh * 2, zoff, ml, tag, true);
            const float ms = uf(ml[0]), ls = uf(ml[1]);
            float M = fmaxf(ms, __shfl_xor_sync(0xffffffffu, ms, 1));
            M = fmaxf(M, __shfl_xor_sync(0xffffffffu, M, 2));
            float L = ls * __expf(ms - M);
            L += __shfl_xor_sync(0xffffffffu, L, 1);
            L += __shfl_xor_sync(0xffffffffu, L, 2);
            sts32_if(s_stats + (32 + uh) * 4, fu(__expf(mloc - M) / L), (lane & ~4) == 0);
        }
        bar_256();
        const float f = lds_f(s_stats + (32 + uh) * 4);
        sts128_if(base + OFF_P + tid * 16, pack2(e[0] * f, e[1] * f), pack2(e[2] * f, e[3] * f), pack2(e[4] * f, e[5] * f),
                  pack2(e[6] * f, e[7] * f), true);
        bar_256();

        float acc[4] = {}, acc2[4] = {};
        const int cc = (warp & 3) * 2 + hi8;
        const uint32_t voff = base + (warp >> 2) * (CH / 2) + rr * 128 + ((cc ^ (lane & 7)) << 4);
        uint32_t poff = base + OFF_P + (g & 1) * 64 + t * 16;
        uint32_t* odst = gs->ex_o + cta * 256 + (t & 1) * 128 + warp * 16 + ((t & 2) << 2) + g;
#pragma unroll 1
        for (int c = 32; c < 64; c++) {
            const int s = c + S0 >= 2 * NS ? c + S0 - 2 * NS : c + S0 - NS;
            if (c == PREWRITE_AT) { st_t1(odst, 0u); prewrite(); }
            const uint4 p0 = lds128(poff);
            poff += 128;
            mbar_wait(bars + 8 * (U_KV + c));
            uint32_t a[4], a2[4];
            ldsm4t(a, voff + s * CH);
            ldsm4t(a2, voff + s * CH + 2048);
            mma(acc, a, p0.x, p0.y);
            mma(acc2, a2, p0.z, p0.w);
            __syncwarp();
            mbar_arrive_if(bars + 8 * (B_USED + c), 1, lane == 0);
        }
        st_t1(odst, tagf(sel4(t, acc[0] + acc2[0], acc[1] + acc2[1], acc[2] + acc2[2], acc[3] + acc2[3]), tg0));
    } else {
        mbar_wait(bars + 8 * (U_KV + PREWRITE_AT));
        prewrite();
    }
    {
#pragma unroll
        for (int ks = 0; ks < 2; ks++) {
            mbar_wait(bars + 8 * (U_WO + 2 * ks)); mbar_wait(bars + 8 * (U_WO + 2 * ks + 1));
#pragma unroll
            for (int mt = 0; mt < 4; mt++) ldsm4t(wf[ks][mt], rowa + OFF_WO + ks * 18432 + (((mt * 2 + hi8) ^ lsw) << 4));
        }
        asm volatile("bar.sync 4, 320;" ::: "memory");
        const uint4 ob = lds128(base + OFF_OB + fb * 64 + t * 16);
        float acc[4][4] = {};
#pragma unroll
        for (int mt = 0; mt < 4; mt++) mma(acc[mt], wf[0][mt], ob.x, ob.y);
#pragma unroll
        for (int mt = 0; mt < 4; mt++) mma(acc[mt], wf[1][mt], ob.z, ob.w);
        publish(acc, tg1);
        announce(cnt[C_AO][lane & (RCNT - 1)], warp == 8 && lane < RCNT0);
    }
    const uint32_t gub = bars + 8 * (U_GU + 2 * (warp / 3));
    const uint32_t gxb = heavy ? bars + 8 * (U_GX + 2 * (warp / 3)) : gub;
    uint32_t dn[3][4][4];
    auto load_gu = [&]() {
        const uint32_t rb = base + OFF_GU + hi8 * 36864 + (warp * 64 + rr) * 64;
#pragma unroll
        for (int ks = 0; ks < 4; ks++)
#pragma unroll
            for (int j = 0; j < 4; j++) ldsm4t(wf[ks][j], rb + ks * 1024 + ((j ^ ((rr >> 1) & 3)) << 4));
        if (heavy) {
            const uint32_t rx = base + OFF_GX + hi8 * 18432 + (warp * 64 + rr) * 32;
#pragma unroll
            for (int ks = 0; ks < 4; ks++)
#pragma unroll
                for (int j = 0; j < 2; j++) ldsm4t(dn[1 + j][ks], rx + ks * 512 + ((j ^ ((rr >> 2) & 1)) << 4));
        }
    };
    auto load_dn = [&](int ks) {
#pragma unroll
        for (int mt = 0; mt < 4; mt++) ldsm4t(dn[ks][mt], rowa + OFF_DN + ks * 18432 + (((mt * 2 + hi8) ^ lsw) << 4));
    };
    auto dn_in = [&](int ks) {
        return __all_sync(0xffffffffu, mbar_test(bars + 8 * (U_DN + 2 * ks)) && mbar_test(bars + 8 * (U_DN + 2 * ks + 1)));
    };
    bool have_gu = false, have_dn = false;
    auto try_gu = [&]() {
        if (!have_gu && __all_sync(0xffffffffu, mbar_test(gxb + 8) && mbar_test(gxb) && mbar_test(gub + 8) && mbar_test(gub))) {
            load_gu();
            have_gu = true;
        }
    };
    auto gate = [&](uint32_t gb) {
        unsigned n = 0;
        while (true) {
            try_gu();
            if (__all_sync(0xffffffffu, have_gu ? mbar_try(gb) : mbar_test(gb))) break;
            if (++n > 64 * SPIN_LIMIT) __trap();
        }
    };
    const uint32_t* rsrc = gs->ex_part + (warp & 7) * 16 * (DM * 2) + cta * 32 + lane;
    float x1r = 0.f;
    if (reducer) {
        gate(bars + 8 * B_GATE_AO);
        if (warp < 8) reduce_part1(rsrc, s_r2, warp, lane, tg1);
        bar_comp();
        if (warp == RED_WARP) {
            x1r = rbf(xr + rbf(gar * rbf(reduce_part2(s_r2, lane))));
            const float other = __shfl_xor_sync(0xffffffffu, x1r, 1);
            st_w1(x1dst, pack2(x1r, other), tag, x1pub);
            announce(cnt[C_X1][lane & (RCNT - 1)], lane < RCNT);
        }
    }
    gate(bars + 8 * B_GATE_X1);
    {
        unsigned long long w0, w1;
        unsigned n = 0;
        while (true) {
            asm volatile("ld.relaxed.gpu.global.b64 %0, [%1];" : "=l"(w0) : "l"(gs->ex_x1 + tid) : "memory");
            asm volatile("ld.relaxed.gpu.global.b64 %0, [%1];" : "=l"(w1) : "l"(gs->ex_x1 + 288 + tid) : "memory");
            try_gu();
            if (!have_dn && dn_in(0)) { load_dn(0); have_dn = true; }
            if (__all_sync(0xffffffffu, (uint32_t)(w0 >> 32) == tag && (uint32_t)(w1 >> 32) == tag)) break;
            if (++n > SPIN_LIMIT) __trap();
        }
        y[0] = bf_lo((uint32_t)w0); y[1] = bf_hi((uint32_t)w0); y[2] = bf_lo((uint32_t)w1); y[3] = bf_hi((uint32_t)w1);
        ln_part1(y, s_stats, warp, lane);
        if (!have_gu) { mbar_wait(gub); mbar_wait(gub + 8); mbar_wait(gxb); mbar_wait(gxb + 8); load_gu(); }
        bar_comp();
        ln_part2(y, s_stats, lane);
        uint32_t bfr[4][2];
        spread_b(bfr, pack2(rbf(y[0] * cbv[0]) + sbv[0], rbf(y[1] * cbv[1]) + sbv[1]),
                 pack2(rbf(y[2] * cbv[2]) + sbv[2], rbf(y[3] * cbv[3]) + sbv[3]), lane);
        const uint32_t red = s_sc + (warp * 48 + g + t * 8) * 16;
        float acc[4][4] = {};
#pragma unroll
        for (int ks = 0; ks < 4; ks++)
#pragma unroll
            for (int j = 0; j < 4; j++) mma(acc[j], wf[ks][j], bfr[ks][0], bfr[ks][1]);
        if (heavy) {
            float ax[2][4] = {};
#pragma unroll
            for (int ks = 0; ks < 4; ks++)
#pragma unroll
                for (int j = 0; j < 2; j++) mma(ax[j], dn[1 + j][ks], bfr[ks][0], bfr[ks][1]);
            sts128_if(red + 512, fu(t ? ax[1][0] : ax[0][0]), fu(t ? ax[1][1] : ax[0][1]), fu(t ? ax[1][2] : ax[0][2]),
                      fu(t ? ax[1][3] : ax[0][3]), t < 2);
        }
        sts128_if(red, fu(sel4(t, acc[0][0], acc[1][0], acc[2][0], acc[3][0])), fu(sel4(t, acc[0][1], acc[1][1], acc[2][1], acc[3][1])),
                  fu(sel4(t, acc[0][2], acc[1][2], acc[2][2], acc[3][2])), fu(sel4(t, acc[0][3], acc[1][3], acc[2][3], acc[3][3])), true);
        asm volatile("bar.arrive 6, 320;" ::: "memory");
    }
    {
        bool got[3];
#pragma unroll
        for (int ks = 0; ks < 3; ks++) {
            got[ks] = ks == 0 && have_dn;
            if (!got[ks] && (ks < 2 || heavy) && dn_in(ks)) { load_dn(ks); got[ks] = true; }
        }
        asm volatile("bar.sync 7, 320;" ::: "memory");
        uint32_t hb[6];
#pragma unroll
        for (int i = 0; i < 6; i++) hb[i] = fu(lds_f(base + OFF_HH + (fb * 32 + t + i * 4) * 4));
        float acc[4][4] = {};
#pragma unroll
        for (int ks = 0; ks < 3; ks++) {
            if (ks < 2 || heavy) {
                if (!got[ks]) {
                    mbar_wait(bars + 8 * (U_DN + 2 * ks)); mbar_wait(bars + 8 * (U_DN + 2 * ks + 1));
                    load_dn(ks);
                }
#pragma unroll
                for (int mt = 0; mt < 4; mt++) mma(acc[mt], dn[ks][mt], hb[2 * ks], hb[2 * ks + 1]);
            }
        }
        publish(acc, tg2);
    }
    if (reducer) {
        if (warp < 8) reduce_part1(rsrc, s_r2, warp, lane, tg2);
        bar_comp();
        if (warp == RED_WARP) {
            const float r = x1r + rbf(gbr * rbf(reduce_part2(s_r2, lane)));
            const float other = __shfl_xor_sync(0xffffffffu, r, 1);
            if (x1pub) *reinterpret_cast<uint32_t*>(out + rb_ * DM + rcol) = pack2(r, other);
            if (cta == 0 && lane == 0) st_t1(&gs->epoch, tag);
        }
    }
}

typedef CUresult (*EncodeFn)(CUtensorMap*, CUtensorMapDataType, cuuint32_t, void*, const cuuint64_t*, const cuuint64_t*,
                             const cuuint32_t*, const cuuint32_t*, CUtensorMapInterleave, CUtensorMapSwizzle,
                             CUtensorMapL2promotion, CUtensorMapFloatOOBfill);

void make_map(EncodeFn enc, CUtensorMap* m, const void* p, uint64_t cols, uint64_t rows, uint32_t bc, uint32_t br,
              CUtensorMapSwizzle sw, CUtensorMapL2promotion prom, bool split_halves = false) {
    cuuint64_t gd[3] = {split_halves ? cols / 2 : cols, rows, split_halves ? 2u : 1u};
    cuuint64_t gs[2] = {cols * 2, split_halves ? cols : cols * 2 * rows};
    cuuint32_t bx[3] = {bc, br, split_halves ? 2u : 1u};
    cuuint32_t es[3] = {1, 1, 1};
    enc(m, CU_TENSOR_MAP_DATA_TYPE_BFLOAT16, 3, const_cast<void*>(p), gd, gs, bx, es, CU_TENSOR_MAP_INTERLEAVE_NONE, sw, prom,
        CU_TENSOR_MAP_FLOAT_OOB_FILL_NONE);
}

void build_ops(uint4* list, bool heavy) {
    constexpr int NMAX = NOPS_HEAVY + NPRE;
    uint4 op[NMAX];
    int order[NMAX], n = 0;
    for (int u = 0; u < 3; u++) order[n++] = heavy ? U_WQ + u : u;
    for (int u = U_KV; u < U_KV + K_AT_START; u++) order[n++] = u;
    if (!heavy) for (int u = 0; u < 3; u++) order[n++] = U_WQ + u;
    for (int u = U_KV + K_AT_START; u < U_WO; u++) order[n++] = u;
    const int n_v = n;
    for (int k = 0; k < 4; k++) order[n++] = U_WO + k;
    for (int k = 0; k < 3; k++) {
        order[n++] = U_GU + 2 * k; order[n++] = U_GU + 2 * k + 1;
        if (heavy) { order[n++] = U_GX + 2 * k; order[n++] = U_GX + 2 * k + 1; }
    }
    for (int k = 0; k < (heavy ? 6 : 4); k++) order[n++] = U_DN + k;
    int kb[NMAX], win[NMAX], cum[NMAX + 1];
    cum[0] = 0;
    for (int i = 0; i < n; i++) {
        const int u = order[i];
        int dst, sel0 = 0, sel1 = 0, row = 0, map, spb = -1;
        win[i] = WIN_TAIL;
        if (u < U_KV || (u >= U_WQ && u < U_GX)) {
            const int k = u < U_KV ? u : u - U_WQ + 3;
            map = k < 3 ? M_WMOD : M_WQ; dst = OFF_WMOD + k * 12288; sel0 = 1; row = (k % 3) * 192; kb[i] = 12;
            spb = B_DONE; win[i] = WIN_MID;
        } else if (u < U_WO) {
            const int c = u - U_KV, slot = (c + S0) % NS;
            map = c < 32 ? M_K : M_V; dst = slot * CH; sel1 = 1; row = ((c & 31) >> 1) * 256 + (c & 1) * 32; kb[i] = 8;
            spb = c >= NS ? B_USED + c - NS : (slot >= 9 && slot <= 13) ? B_WQFREE : (slot >= 5 && slot < 9) ? B_MODFREE : B_DONE;
            win[i] = c < 64 - END_CHUNKS ? WIN_MID : WIN_END;
        } else if (u < U_GU) {
            const int k = u - U_WO;
            map = M_WO; dst = OFF_WO + k * 9216; sel1 = 4; row = k * 72; kb[i] = 9; win[i] = WIN_END;
        } else if (u < U_WQ) {
            const int k = u - U_GU;
            map = M_GATE + (k & 1); dst = OFF_GU + (k & 1) * 36864 + (k >> 1) * 12288; sel0 = 1; row = (k >> 1) * 192; kb[i] = 12;
        } else if (u < U_DN) {
            const int k = u - U_GX;
            map = M_GATEX + (k & 1); dst = OFF_GX + (k & 1) * 18432 + (k >> 1) * 6144; sel0 = 2; row = (k >> 1) * 192; kb[i] = 6;
        } else {
            const int k = u - U_DN;
            map = M_DN; dst = OFF_DN + k * 9216; kb[i] = 9; win[i] = WIN_LAST;
            if (k < 4) { sel1 = 4; row = k * 72; } else { sel1 = 5; row = (k - 4) * 72; }
        }
        if (heavy && i >= n_v) win[i] += WIN_HEAVY_EXTRA;
        if (spb < 0) spb = B_USED + 64 - NS + ((dst + kb[i] * 1024 - 1) >> 13);
        cum[i + 1] = cum[i] + kb[i];
        op[i].x = (dst >> 8) | (sel0 << 10) | (sel1 << 12) | (map << 15) | (kb[i] << 19) | ((unsigned)u << 24) |
                  ((i == n_v - ANCHOR_BACK || i == n_v - ANCHOR_BACK + 1) ? 1u << 23 : 0u);
        op[i].y = row | (spb << 12);
    }
    const double tv = heavy ? PACE_TV_HEAVY : PACE_TV;
    for (int i = 0; i < n; i++) {
        double due = i <= n_v ? PACE_T0 + (tv - PACE_T0) * cum[i] / cum[n_v] : tv + (PACE_TE - tv) * (cum[i] - cum[n_v]) / (cum[n] - cum[n_v]);
        if (due < 0) due = 0;
        op[i].y |= (unsigned)(due / 16) << 20;
        unsigned long long lv = 0;
        for (int l = 0; l < 8; l++) {
            int w = win[i] + (l - PACE_MID) * PACE_STEP, wd = B_DONE;
            if (w < PACE_WMIN) w = PACE_WMIN;
            if (w > PACE_WMAX) w = PACE_WMAX;
            if (i >= n_v && w > win[i] + TAIL_UP) w = win[i] + TAIL_UP;
            for (int j = i - 1; j >= 0; j--)
                if (cum[i + 1] - cum[j] > w) { wd = order[j]; break; }
            lv |= (unsigned long long)wd << (8 * l);
        }
        op[i].z = (unsigned)lv;
        op[i].w = (unsigned)(lv >> 32);
        if (i >= NPRE) list[i - NPRE] = op[i];
    }
}

}

extern "C" void kernel_launch(void* const* d_in, const int* in_sizes, int n_in, void* d_out, int out_size) {
    (void)in_sizes; (void)n_in; (void)out_size;
    const __nv_bfloat16* x = (const __nv_bfloat16*)d_in[0];
    const __nv_bfloat16* kc = (const __nv_bfloat16*)d_in[1];
    const __nv_bfloat16* vc = (const __nv_bfloat16*)d_in[2];
    const __nv_bfloat16* wq = (const __nv_bfloat16*)d_in[3];
    const __nv_bfloat16* wo = (const __nv_bfloat16*)d_in[4];
    const __nv_bfloat16* wg = (const __nv_bfloat16*)d_in[6];
    const __nv_bfloat16* wu = (const __nv_bfloat16*)d_in[7];
    const __nv_bfloat16* wd = (const __nv_bfloat16*)d_in[8];
    const __nv_bfloat16* cv = (const __nv_bfloat16*)d_in[9];
    const __nv_bfloat16* wm = (const __nv_bfloat16*)d_in[10];

    EncodeFn enc = nullptr;
    cudaDriverEntryPointQueryResult qr;
    cudaGetDriverEntryPoint("cuTensorMapEncodeTiled", (void**)&enc, cudaEnableDefault, &qr);
    cudaFuncSetAttribute(fused_block_kernel, cudaFuncAttributeMaxDynamicSharedMemorySize, SMEM_BYTES);
    Params mp;
    const CUtensorMapL2promotion P128 = CU_TENSOR_MAP_L2_PROMOTION_L2_128B, P256 = CU_TENSOR_MAP_L2_PROMOTION_L2_256B;
    make_map(enc, &mp.m[M_WMOD], wm, 6 * DM, DM, 32, 192, CU_TENSOR_MAP_SWIZZLE_64B, P128);
    make_map(enc, &mp.m[M_WQ], wq, 4096, DM, 32, 192, CU_TENSOR_MAP_SWIZZLE_64B, P128);
    make_map(enc, &mp.m[M_K], kc, 128, (uint64_t)2 * 16 * SK, 128, 32, CU_TENSOR_MAP_SWIZZLE_NONE, P256);
    make_map(enc, &mp.m[M_V], vc, 128, (uint64_t)2 * 16 * SK, 64, 32, CU_TENSOR_MAP_SWIZZLE_128B, P256, true);
    make_map(enc, &mp.m[M_WO], wo, 64, 4096 * 9, 64, 72, CU_TENSOR_MAP_SWIZZLE_128B, P256);
    make_map(enc, &mp.m[M_DN], wd, 64, FF * 9, 64, 72, CU_TENSOR_MAP_SWIZZLE_128B, P256);
    make_map(enc, &mp.m[M_GATE], wg, FF, DM, 32, 192, CU_TENSOR_MAP_SWIZZLE_64B, P128);
    make_map(enc, &mp.m[M_UP], wu, FF, DM, 32, 192, CU_TENSOR_MAP_SWIZZLE_64B, P128);
    make_map(enc, &mp.m[M_GATEX], wg, FF, DM, 16, 192, CU_TENSOR_MAP_SWIZZLE_32B, P128);
    make_map(enc, &mp.m[M_UPX], wu, FF, DM, 16, 192, CU_TENSOR_MAP_SWIZZLE_32B, P128);
    build_ops(mp.op, false);
    build_ops(mp.op + NOPS_LIGHT, true);
    for (int i = 3; i < 9; i++) {
        const int blk = i / 3, bar = (blk == 1 ? U_WQ : 3) + i % 3;
        mp.op[NOPS_LIGHT + NOPS_HEAVY + i - 3] =
            make_uint4(((OFF_WMOD + i * 12288) >> 8) | ((blk + 1) << 10) | (M_WMOD << 15) | (12 << 19) | (bar << 24),
                       (i % 3) * 192 | (B_DONE << 12), B_DONE * 0x01010101u, B_DONE * 0x01010101u);
    }
    Scratch* gs = nullptr;
    cudaGetSymbolAddress((void**)&gs, g_scratch);
    fused_block_kernel<<<NCTA + NHELP, NTHR, SMEM_BYTES>>>(x, cv, (__nv_bfloat16*)d_out, gs, (const char*)kc, mp);
}
```
